```python
import torch

def _softmax(x, axis=-1):
    return torch.softmax(x, dim=axis)

def _gelu(x):
    return torch.nn.functional.gelu(x, approximate='tanh')

def _silu(x):
    return torch.nn.functional.silu(x)

def _sigmoid(x):
    return torch.sigmoid(x)

def _layernorm(x, axis=-1, eps=1e-05):
    m = x.mean(dim=axis, keepdim=True)
    v = x.var(dim=axis, keepdim=True, unbiased=False)
    return (x - m) / torch.sqrt(v + eps)

def _scatter_add(tgt, idx, src, axis=0):
    return tgt.clone().index_add_(axis, idx, src)

def _segment_sum(src, seg, n):
    out = torch.zeros((n,) + src.shape[1:], dtype=src.dtype)
    return out.index_add_(0, seg, src)

def _pad(x, pw):
    flat = tuple((v for pair in reversed(pw) for v in pair))
    return torch.nn.functional.pad(x, flat)
kernel_name = 'adaLN_cond__memory_aug_recurrent_mem_tr__glu_gated_geglu__prompt'

def setup_inputs():

    _w = lambda a: (lambda t: t.to(torch.bfloat16) if t.is_floating_point() else t)(torch.as_tensor(a))

    def _A_setup():
        B, S, Dm = (1, 2048, 512)
        H, Dh = (32, 128)
        M, seg = (8, 32)
        seg = min(seg, S)
        S = S // seg * seg
        return {'x': _w((lambda *s: torch.randn(*s, dtype=torch.bfloat16) * 0.05)(B, S, Dm)), 'mem0': _w((lambda *s: torch.randn(*s, dtype=torch.bfloat16) * 0.8)(B, M, Dm)), 'Wq': _w((lambda *s: torch.randn(*s, dtype=torch.bfloat16) * 1.6)(Dm, H, Dh) * Dm ** (-0.5)), 'Wk': _w((lambda *s: torch.randn(*s, dtype=torch.bfloat16) * 1.6)(Dm, H, Dh) * Dm ** (-0.5)), 'Wv': _w((lambda *s: torch.randn(*s, dtype=torch.bfloat16) * 0.8)(Dm, H, Dh) * Dm ** (-0.5)), 'Wo': _w((lambda *s: torch.randn(*s, dtype=torch.bfloat16) * 0.8)(H, Dh, Dm) * (H * Dh) ** (-0.5)), 'seg_len': seg}
    _A_in = _A_setup()

    def _B_setup():
        B, S, Dm, Df = (1, 2048, 512, 1792)
        return {'x': _w((lambda *s: torch.randn(*s, dtype=torch.bfloat16) * 0.05)(B, S, Dm)), 'w_gate': _w((lambda *s: torch.randn(*s, dtype=torch.bfloat16) * 0.8)(Dm, Df) * Dm ** (-0.5)), 'w_up': _w((lambda *s: torch.randn(*s, dtype=torch.bfloat16) * 0.8)(Dm, Df) * Dm ** (-0.5)), 'w_down': _w((lambda *s: torch.randn(*s, dtype=torch.bfloat16) * 0.8)(Df, Dm) * Df ** (-0.5))}
    _B_in = _B_setup()
    return {'A_x': _A_in['x'], 'A_mem0': _A_in['mem0'], 'A_Wq': _A_in['Wq'], 'A_Wk': _A_in['Wk'], 'A_Wv': _A_in['Wv'], 'A_Wo': _A_in['Wo'], 'A_seg_len': _A_in['seg_len'], 'B_x': _B_in['x'], 'B_w_gate': _B_in['w_gate'], 'B_w_up': _B_in['w_up'], 'B_w_down': _B_in['w_down'], 'c': _w((lambda *s: torch.randn(*s, dtype=torch.bfloat16) * 0.1)(1, 512) * 8.0), 'w_mod': _w((lambda *s: torch.randn(*s, dtype=torch.bfloat16) * 0.1)(512, 6 * 512) * 512 ** (-0.5) * 8.0)}

def reference(A_x, A_mem0, A_Wq, A_Wk, A_Wv, A_Wo, A_seg_len, B_x, B_w_gate, B_w_up, B_w_down, c, w_mod):

    def _A_ref(x, mem0, Wq, Wk, Wv, Wo, seg_len):
        B, S, Dm = x.shape
        H, Dh = (Wq.shape[1], Wq.shape[2])
        M = mem0.shape[1]
        scale = Dh ** (-0.5)
        n_seg = S // seg_len
        L = M + seg_len
        idx = torch.arange(L)
        mask = (idx[:, None] < M) | (idx[:, None] >= idx[None, :])
        mem = mem0
        outs = []
        for s in range(n_seg):
            xs = x[:, s * seg_len:(s + 1) * seg_len, :].clone()
            h = torch.concatenate([mem, xs], axis=1)
            q = torch.einsum('btd,dhe->bhte', h, Wq)
            k = torch.einsum('btd,dhe->bhte', h, Wk)
            v = torch.einsum('btd,dhe->bhte', h, Wv)
            scores = torch.einsum('bhqe,bhke->bhqk', q, k) * scale
            scores = torch.where(mask[None, None], scores, -1000000000.0)
            p = _softmax(scores, axis=-1)
            o = torch.einsum('bhqk,bhke->bhqe', p, v)
            o = torch.einsum('bhte,hed->btd', o, Wo)
            mem = o[:, :M, :].clone()
            outs.append(o[:, M:, :])
        return torch.concatenate(outs, axis=1)

    def _B_ref(x, w_gate, w_up, w_down):
        g = torch.einsum('bsd,df->bsf', x, w_gate)
        u = torch.einsum('bsd,df->bsf', x, w_up)
        h = _gelu(g) * u
        return torch.einsum('bsf,fd->bsd', h, w_down)
    x = A_x
    mod = (_silu(c) @ w_mod).reshape(c.shape[0], 6, 1, -1)
    sa, ca, ga, sb, cb, gb = (mod[:, 0].clone(), mod[:, 1].clone(), mod[:, 2].clone(), mod[:, 3].clone(), mod[:, 4].clone(), mod[:, 5].clone())
    h = _layernorm(x, axis=-1) * (1 + ca) + sa
    x = x + ga * _A_ref(h, A_mem0, A_Wq, A_Wk, A_Wv, A_Wo, A_seg_len)
    h = _layernorm(x, axis=-1) * (1 + cb) + sb
    x = x + gb * _B_ref(h, B_w_gate, B_w_up, B_w_down)
    return x
```

```cpp
#include <cuda_runtime.h>
#include <cuda_bf16.h>
#include <cuda_fp16.h>
#include <cuda.h>
#include <stdint.h>
#include <string.h>

namespace {

typedef __nv_bfloat16 bf16;

constexpr int S_ = 2048, D_ = 512, H_ = 32, NSEG = 64, F_ = 1792;
constexpr int NTHREADS = 384;
constexpr int NCHAIN = 32;
constexpr int XCH_BYTES = 20736;
constexpr int MAX_SK1 = 16, MAX_SK2 = 7;

__device__ __align__(1024) float g_mod[6 * D_];
__device__ __align__(1024) bf16 g_h[S_ * D_];
__device__ __align__(1024) bf16 g_qkv[(size_t)NSEG * H_ * 2 * 32 * 128];
__device__ __align__(1024) bf16 g_o[(size_t)S_ * 4096];
__device__ __align__(1024) uint4 g_q[(size_t)16 * H_ * 8 * 8 * 32];
__device__ __align__(1024) unsigned char g_xch[NSEG * XCH_BYTES];
__device__ __align__(1024) unsigned char g_kvm[NSEG * H_ * 4096];
__device__ __align__(1024) bf16 g_p1[(size_t)MAX_SK1 * S_ * D_];
__device__ __align__(1024) float g_x1[S_ * D_];
__device__ __align__(1024) bf16 g_h2[S_ * D_];
__device__ __align__(1024) bf16 g_act[S_ * F_];
__device__ __align__(1024) bf16 g_p2[(size_t)MAX_SK2 * S_ * D_];

enum {
    F_MOD = 0, F_ZERO = 32, F_EXIT = 64, F_HALL = 96, F_NEAR = 352, F_QD = 160,
    F_H = 128,
    F_DONE = 256,
    F_CLAIM = 384,
    F_QKV = 512,
    NFLAGS = F_QKV + 1024
};
__device__ __align__(1024) unsigned g_flags[NFLAGS];
#define DBG0D(cond, idx, dep) do { } while (0)
#define DBG0C(cond, idx, dep) do { } while (0)
#define DBGC(cond, idx, val) do { } while (0)
#define DBG(cond, idx, val) do { } while (0)
#define DBGD(cond, idx, dep) do { } while (0)

struct Params {
    CUtensorMap tmWq, tmWk, tmWv, tmWo, tmG, tmU, tmDn, tmO, tmH2, tmAct;
    const bf16* x; const bf16* mem0; const bf16* c; const bf16* wmod; bf16* out;
    int mode; int delay; int nclusters; int zero;
    unsigned char need[128], cnt[128], prio[128];
    unsigned char nh[16], sk1[16], sk2[16], rs[16];
    int qpre0;
    int fine0;
};
enum { T_ATT = 0, T_WO = 1, T_LN2 = 2, T_FFN1 = 3, T_FFN2 = 4, T_FIN = 5, T_QKV = 6, T_Q = 7 };
constexpr uint32_t TASK_END = 0xfff;
__host__ __device__ constexpr int qkv_t0(int c) { return c == 0 ? 0 : 32; }

constexpr uint32_t C_WK = 0, C_WO = 65536, C_WQ = 131072;
constexpr uint32_t C_KV = 163840;
constexpr uint32_t C_MEM = 212992, C_SQ = 221184, C_SKM = 223232, C_SVM = 225280, C_SO = 227328, C_XP = C_SO;
constexpr uint32_t C_STAGE = C_KV;
constexpr uint32_t W_B = 0, W_RING1 = 131072;
constexpr uint32_t W_KVM = 196608;
constexpr uint32_t W_GB = 229376;
constexpr uint32_t STAGE2 = 49152;
constexpr uint32_t BAR = 231424;
enum {
    MB_W0 = 0, MB_W1, MB_W2, MB_QKR, MB_V, MB_KV, MB_KV1, MB_KV2,
    MB_RED,
    MB_MEM,
    MB_PD,
    MB_QD,
    MB_P0,
    MB_BW,
    MB_F1 = MB_BW + 8, MB_E1 = MB_F1 + 8,
    MB_F2 = MB_E1 + 8, MB_E2 = MB_F2 + 4,
    MB_AF = MB_E2 + 4, MB_AE = MB_AF + 8,
    MB_SD1 = MB_AE + 8,
    MB_SD2 = MB_SD1 + 2,
    MB_TF = MB_SD2 + 1,
    MB_TE = MB_TF + 2,
    MB_COUNT = MB_TE + 2
};
constexpr uint32_t TSLOT = BAR + 640;
constexpr uint32_t C_SL = BAR + 704;
constexpr uint32_t C_TGT = BAR + 768;
constexpr uint32_t W_TILES = BAR + 800;
constexpr uint32_t SMEM_BYTES = BAR + 1024;

__device__ __forceinline__ uint32_t smem_u32(const void* p) { return (uint32_t)__cvta_generic_to_shared(p); }
__device__ __forceinline__ uint32_t mapa(uint32_t a, uint32_t r) {
    uint32_t o; asm volatile("mapa.shared::cluster.u32 %0, %1, %2;" : "=r"(o) : "r"(a), "r"(r)); return o;
}
__device__ __forceinline__ void mbar_init(uint32_t b, uint32_t c) { asm volatile("mbarrier.init.shared::cta.b64 [%0], %1;" :: "r"(b), "r"(c) : "memory"); }
__device__ __forceinline__ void mbar_expect(uint32_t b, uint32_t bytes) {
    asm volatile("mbarrier.arrive.expect_tx.shared::cta.b64 _, [%0], %1;" :: "r"(b), "r"(bytes) : "memory");
}
__device__ __forceinline__ void mbar_expect_remote(uint32_t cluster_addr, uint32_t bytes) {
    asm volatile("mbarrier.arrive.expect_tx.shared::cluster.b64 _, [%0], %1;" :: "r"(cluster_addr), "r"(bytes) : "memory");
}
__device__ __forceinline__ void mbar_arrive(uint32_t b) { asm volatile("mbarrier.arrive.shared::cta.b64 _, [%0];" :: "r"(b) : "memory"); }
__device__ __forceinline__ void mbar_arrive_remote(uint32_t cluster_addr) {
    asm volatile("mbarrier.arrive.shared::cluster.b64 _, [%0];" :: "r"(cluster_addr) : "memory");
}
__device__ __forceinline__ bool mbar_try(uint32_t b, uint32_t ph) {
    uint32_t p;
    asm volatile("{\n.reg .pred p;\nmbarrier.try_wait.parity.shared::cta.b64 p, [%1], %2;\nselp.u32 %0, 1, 0, p;\n}"
                 : "=r"(p) : "r"(b), "r"(ph) : "memory");
    return p != 0;
}
__device__ __forceinline__ bool mbar_test(uint32_t b, uint32_t ph) {
    uint32_t p;
    asm volatile("{\n.reg .pred p;\nmbarrier.test_wait.parity.shared::cta.b64 p, [%1], %2;\nselp.u32 %0, 1, 0, p;\n}"
                 : "=r"(p) : "r"(b), "r"(ph) : "memory");
    return p != 0;
}
__device__ __forceinline__ unsigned ld_volatile_u32(const unsigned* p) {
    unsigned v; asm volatile("ld.volatile.global.u32 %0, [%1];" : "=r"(v) : "l"(p) : "memory"); return v;
}
constexpr long long WAIT_LIMIT = 400000000LL;
__device__ __forceinline__ void wait_check(long long t0, int site) {
    if (clock64() - t0 > WAIT_LIMIT) {
        __trap();
    }
}
__device__ __forceinline__ void mbar_wait_(uint32_t b, uint32_t ph, int) {
    asm volatile("{\n.reg .pred p;\n.reg .u32 c;\nmov.u32 c, 0;\n"
                 "W_%=:\nmbarrier.try_wait.parity.shared::cta.b64 p, [%0], %1;\n@p bra D_%=;\n"
                 "add.u32 c, c, 1;\nsetp.lt.u32 p, c, 8388608;\n@p bra W_%=;\ntrap;\nD_%=:\n}"
                 :: "r"(b), "r"(ph) : "memory");
}
#define mbar_wait(b, ph) mbar_wait_(b, ph, __LINE__)
__device__ __forceinline__ void flag_wait_(const unsigned* flag, unsigned target, int site) {
    if (ld_volatile_u32(flag) < target) {
        const long long t0 = clock64();
        for (unsigned it = 1;; ++it) {
            __nanosleep(64);
            if (ld_volatile_u32(flag) >= target) break;
            if ((it & 63u) == 0) wait_check(t0, site);
        }
    }
    asm volatile("fence.acquire.gpu;" ::: "memory");
    asm volatile("fence.proxy.async.global;" ::: "memory");
}
#define flag_wait(f, t) flag_wait_(f, t, __LINE__)
__device__ __forceinline__ void flag_signal(unsigned* flag) {
    asm volatile("fence.proxy.async.global;" ::: "memory");
    asm volatile("red.release.gpu.global.add.u32 [%0], 1;" :: "l"(flag) : "memory");
}
__device__ __forceinline__ bool elect_one() {
    uint32_t p;
    asm volatile("{\n.reg .pred p;\nelect.sync _|p, 0xffffffff;\nselp.u32 %0, 1, 0, p;\n}" : "=r"(p));
    return p != 0;
}
__device__ __forceinline__ uint32_t cta_rank() { uint32_t r; asm volatile("mov.u32 %0, %%cluster_ctarank;" : "=r"(r)); return r; }
__device__ __forceinline__ uint32_t cluster_id() { uint32_t r; asm volatile("mov.u32 %0, %%clusterid.x;" : "=r"(r)); return r; }
__device__ __forceinline__ uint32_t gtime32() { uint32_t r; asm volatile("mov.u32 %0, %%globaltimer_lo;" : "=r"(r)); return r; }
__device__ __forceinline__ uint32_t tid_x() { uint32_t r; asm volatile("mov.u32 %0, %%tid.x;" : "=r"(r)); return r; }
__device__ __forceinline__ uint32_t lane_id() { uint32_t r; asm volatile("mov.u32 %0, %%laneid;" : "=r"(r)); return r; }
__device__ __forceinline__ void fence_proxy_async() { asm volatile("fence.proxy.async.global;" ::: "memory"); }
__device__ __forceinline__ void bar_sync(int id, int n) { asm volatile("bar.sync %0, %1;" :: "r"(id), "r"(n) : "memory"); }
__device__ __forceinline__ void bar_arrive(int id, int n) { asm volatile("bar.arrive %0, %1;" :: "r"(id), "r"(n) : "memory"); }
__device__ __forceinline__ void cluster_sync() {
    asm volatile("barrier.cluster.arrive.aligned;\nbarrier.cluster.wait.aligned;" ::: "memory");
}
__device__ __forceinline__ void cluster_sync_relaxed() {
    asm volatile("barrier.cluster.arrive.relaxed.aligned;\nbarrier.cluster.wait.aligned;" ::: "memory");
}
__device__ __forceinline__ void tma2d(uint32_t dst, const CUtensorMap* tm, int c0, int c1, uint32_t mbar) {
    asm volatile("cp.async.bulk.tensor.2d.shared::cluster.global.mbarrier::complete_tx::bytes [%0], [%1, {%3, %4}], [%2];"
                 :: "r"(dst), "l"(tm), "r"(mbar), "r"(c0), "r"(c1) : "memory");
}
__device__ __forceinline__ void tma2d_mc(uint32_t dst, const CUtensorMap* tm, int c0, int c1, uint32_t mbar, uint16_t mask) {
    asm volatile("cp.async.bulk.tensor.2d.shared::cluster.global.mbarrier::complete_tx::bytes.multicast::cluster [%0], [%1, {%3, %4}], [%2], %5;"
                 :: "r"(dst), "l"(tm), "r"(mbar), "r"(c0), "r"(c1), "h"(mask) : "memory");
}
__device__ __forceinline__ void bulk_g2s(uint32_t dst, const void* src, uint32_t bytes, uint32_t mbar) {
    asm volatile("cp.async.bulk.shared::cluster.global.mbarrier::complete_tx::bytes [%0], [%1], %2, [%3];"
                 :: "r"(dst), "l"(src), "r"(bytes), "r"(mbar) : "memory");
}
__device__ __forceinline__ void bulk_g2s_mc(uint32_t dst, const void* src, uint32_t bytes, uint32_t mbar, uint16_t mask) {
    asm volatile("cp.async.bulk.shared::cluster.global.mbarrier::complete_tx::bytes.multicast::cluster [%0], [%1], %2, [%3], %4;"
                 :: "r"(dst), "l"(src), "r"(bytes), "r"(mbar), "h"(mask) : "memory");
}
__device__ __forceinline__ void bulk_prefetch_l2(const void* src, uint32_t bytes) {
    asm volatile("cp.async.bulk.prefetch.L2.global [%0], %1;" :: "l"(src), "r"(bytes) : "memory");
}
__device__ __forceinline__ void st_async_b32(uint32_t a, uint32_t v, uint32_t mb) {
    asm volatile("st.async.weak.shared::cluster.mbarrier::complete_tx::bytes.b32 [%0], %1, [%2];" :: "r"(a), "r"(v), "r"(mb) : "memory");
}
__device__ __forceinline__ void sts32(uint32_t a, uint32_t v) { asm volatile("st.shared.b32 [%0], %1;" :: "r"(a), "r"(v) : "memory"); }
__device__ __forceinline__ void sts64(uint32_t a, uint32_t x, uint32_t y) { asm volatile("st.shared.v2.b32 [%0], {%1, %2};" :: "r"(a), "r"(x), "r"(y) : "memory"); }
__device__ __forceinline__ uint32_t lds32(uint32_t a) { uint32_t v; asm volatile("ld.shared.b32 %0, [%1];" : "=r"(v) : "r"(a) : "memory"); return v; }
__device__ __forceinline__ uint2 lds64v(uint32_t a) {
    uint2 v; asm volatile("ld.volatile.shared.v2.b32 {%0,%1}, [%2];" : "=r"(v.x), "=r"(v.y) : "r"(a) : "memory"); return v;
}
__device__ __forceinline__ uint4 lds128(uint32_t a) {
    uint4 v; asm volatile("ld.shared.v4.b32 {%0,%1,%2,%3}, [%4];" : "=r"(v.x), "=r"(v.y), "=r"(v.z), "=r"(v.w) : "r"(a) : "memory"); return v;
}
__device__ __forceinline__ void ldsm4(uint32_t& r0, uint32_t& r1, uint32_t& r2, uint32_t& r3, uint32_t a) {
    asm volatile("ldmatrix.sync.aligned.m8n8.x4.shared.b16 {%0,%1,%2,%3}, [%4];" : "=r"(r0), "=r"(r1), "=r"(r2), "=r"(r3) : "r"(a) : "memory");
}
__device__ __forceinline__ void ldsm4t(uint32_t& r0, uint32_t& r1, uint32_t& r2, uint32_t& r3, uint32_t a) {
    asm volatile("ldmatrix.sync.aligned.m8n8.x4.trans.shared.b16 {%0,%1,%2,%3}, [%4];" : "=r"(r0), "=r"(r1), "=r"(r2), "=r"(r3) : "r"(a) : "memory");
}
__device__ __forceinline__ uint32_t movm(uint32_t a) {
    uint32_t d; asm volatile("movmatrix.sync.aligned.m8n8.trans.b16 %0, %1;" : "=r"(d) : "r"(a)); return d;
}
__device__ __forceinline__ void mma(float (&d)[4], uint32_t a0, uint32_t a1, uint32_t a2, uint32_t a3, uint32_t b0, uint32_t b1) {
    asm volatile("mma.sync.aligned.m16n8k16.row.col.f32.bf16.bf16.f32 {%0,%1,%2,%3}, {%4,%5,%6,%7}, {%8,%9}, {%0,%1,%2,%3};"
                 : "+f"(d[0]), "+f"(d[1]), "+f"(d[2]), "+f"(d[3]) : "r"(a0), "r"(a1), "r"(a2), "r"(a3), "r"(b0), "r"(b1));
}
__device__ __forceinline__ void mma_h(float (&d)[4], uint32_t a0, uint32_t a1, uint32_t a2, uint32_t a3, uint32_t b0, uint32_t b1) {
    asm volatile("mma.sync.aligned.m16n8k16.row.col.f32.f16.f16.f32 {%0,%1,%2,%3}, {%4,%5,%6,%7}, {%8,%9}, {%0,%1,%2,%3};"
                 : "+f"(d[0]), "+f"(d[1]), "+f"(d[2]), "+f"(d[3]) : "r"(a0), "r"(a1), "r"(a2), "r"(a3), "r"(b0), "r"(b1));
}
__device__ __forceinline__ void sts128(uint32_t a, uint4 v) {
    asm volatile("st.shared.v4.b32 [%0], {%1,%2,%3,%4};" :: "r"(a), "r"(v.x), "r"(v.y), "r"(v.z), "r"(v.w) : "memory");
}
__device__ __forceinline__ uint32_t pack_bf16(float lo, float hi) {
    uint32_t r; asm("cvt.rn.bf16x2.f32 %0, %1, %2;" : "=r"(r) : "f"(hi), "f"(lo)); return r;
}
__device__ __forceinline__ uint32_t pack_f16(float lo, float hi) {
    uint32_t r; asm("cvt.rn.f16x2.f32 %0, %1, %2;" : "=r"(r) : "f"(hi), "f"(lo)); return r;
}
__device__ __forceinline__ float bf_lo(uint32_t v) { return __uint_as_float(v << 16); }
__device__ __forceinline__ float bf_hi(uint32_t v) { return __uint_as_float(v & 0xffff0000u); }
__device__ __forceinline__ uint32_t bf2h(uint32_t v) { return pack_f16(bf_lo(v), bf_hi(v)); }
__device__ __forceinline__ float bf_round(float v) { return __bfloat162float(__float2bfloat16_rn(v)); }
__device__ __forceinline__ float ex2(float x) { float y; asm("ex2.approx.ftz.f32 %0, %1;" : "=f"(y) : "f"(x)); return y; }
__device__ __forceinline__ uint4 ldv128(const void* p) {
    uint4 v; asm volatile("ld.volatile.global.v4.u32 {%0,%1,%2,%3}, [%4];" : "=r"(v.x), "=r"(v.y), "=r"(v.z), "=r"(v.w) : "l"(p) : "memory"); return v;
}
__device__ __forceinline__ uint2 ldv64(const void* p) {
    uint2 v; asm volatile("ld.volatile.global.v2.u32 {%0,%1}, [%2];" : "=r"(v.x), "=r"(v.y) : "l"(p) : "memory"); return v;
}
__device__ __forceinline__ uint64_t gmma_desc(uint32_t addr, uint32_t lbo, uint32_t sbo, uint32_t swz) {
    return (uint64_t)((addr & 0x3FFFF) >> 4) | ((uint64_t)(lbo >> 4) << 16) | ((uint64_t)(sbo >> 4) << 32) | ((uint64_t)swz << 62);
}
__device__ __forceinline__ void wg_fence() { asm volatile("wgmma.fence.sync.aligned;" ::: "memory"); }
__device__ __forceinline__ void wg_commit() { asm volatile("wgmma.commit_group.sync.aligned;" ::: "memory"); }
template <int N> __device__ __forceinline__ void wg_wait() { asm volatile("wgmma.wait_group.sync.aligned %0;" :: "n"(N) : "memory"); }

__device__ __forceinline__ void wgmma_n256(float (&d)[128], uint64_t da, uint64_t db) {
    asm volatile("wgmma.mma_async.sync.aligned.m64n256k16.f32.bf16.bf16 "
        "{%0, %1, %2, %3, %4, %5, %6, %7, %8, %9, %10, %11, %12, %13, %14, %15, %16, %17, %18, %19, %20, %21, %22, %23, %24, %25, %26, %27, %28, %29, %30, %31, %32, %33, %34, %35, %36, %37, %38, %39, %40, %41, %42, %43, %44, %45, %46, %47, %48, %49, %50, %51, %52, %53, %54, %55, %56, %57, %58, %59, %60, %61, %62, %63, %64, %65, %66, %67, %68, %69, %70, %71, %72, %73, %74, %75, %76, %77, %78, %79, %80, %81, %82, %83, %84, %85, %86, %87, %88, %89, %90, %91, %92, %93, %94, %95, %96, %97, %98, %99, %100, %101, %102, %103, %104, %105, %106, %107, %108, %109, %110, %111, %112, %113, %114, %115, %116, %117, %118, %119, %120, %121, %122, %123, %124, %125, %126, %127}, "
        "%128, %129, 1, 1, 1, 0, 1;\n"
        : "+f"(d[0]), "+f"(d[1]), "+f"(d[2]), "+f"(d[3]), "+f"(d[4]), "+f"(d[5]), "+f"(d[6]), "+f"(d[7]), "+f"(d[8]), "+f"(d[9]), "+f"(d[10]), "+f"(d[11]), "+f"(d[12]), "+f"(d[13]), "+f"(d[14]), "+f"(d[15]), "+f"(d[16]), "+f"(d[17]), "+f"(d[18]), "+f"(d[19]), "+f"(d[20]), "+f"(d[21]), "+f"(d[22]), "+f"(d[23]), "+f"(d[24]), "+f"(d[25]), "+f"(d[26]), "+f"(d[27]), "+f"(d[28]), "+f"(d[29]), "+f"(d[30]), "+f"(d[31]), "+f"(d[32]), "+f"(d[33]), "+f"(d[34]), "+f"(d[35]), "+f"(d[36]), "+f"(d[37]), "+f"(d[38]), "+f"(d[39]), "+f"(d[40]), "+f"(d[41]), "+f"(d[42]), "+f"(d[43]), "+f"(d[44]), "+f"(d[45]), "+f"(d[46]), "+f"(d[47]), "+f"(d[48]), "+f"(d[49]), "+f"(d[50]), "+f"(d[51]), "+f"(d[52]), "+f"(d[53]), "+f"(d[54]), "+f"(d[55]), "+f"(d[56]), "+f"(d[57]), "+f"(d[58]), "+f"(d[59]), "+f"(d[60]), "+f"(d[61]), "+f"(d[62]), "+f"(d[63]), "+f"(d[64]), "+f"(d[65]), "+f"(d[66]), "+f"(d[67]), "+f"(d[68]), "+f"(d[69]), "+f"(d[70]), "+f"(d[71]), "+f"(d[72]), "+f"(d[73]), "+f"(d[74]), "+f"(d[75]), "+f"(d[76]), "+f"(d[77]), "+f"(d[78]), "+f"(d[79]), "+f"(d[80]), "+f"(d[81]), "+f"(d[82]), "+f"(d[83]), "+f"(d[84]), "+f"(d[85]), "+f"(d[86]), "+f"(d[87]), "+f"(d[88]), "+f"(d[89]), "+f"(d[90]), "+f"(d[91]), "+f"(d[92]), "+f"(d[93]), "+f"(d[94]), "+f"(d[95]), "+f"(d[96]), "+f"(d[97]), "+f"(d[98]), "+f"(d[99]), "+f"(d[100]), "+f"(d[101]), "+f"(d[102]), "+f"(d[103]), "+f"(d[104]), "+f"(d[105]), "+f"(d[106]), "+f"(d[107]), "+f"(d[108]), "+f"(d[109]), "+f"(d[110]), "+f"(d[111]), "+f"(d[112]), "+f"(d[113]), "+f"(d[114]), "+f"(d[115]), "+f"(d[116]), "+f"(d[117]), "+f"(d[118]), "+f"(d[119]), "+f"(d[120]), "+f"(d[121]), "+f"(d[122]), "+f"(d[123]), "+f"(d[124]), "+f"(d[125]), "+f"(d[126]), "+f"(d[127])
        : "l"(da), "l"(db));
}

__device__ __forceinline__ void wgmma_n128(float (&d)[64], uint64_t da, uint64_t db) {
    asm volatile("wgmma.mma_async.sync.aligned.m64n128k16.f32.bf16.bf16 "
        "{%0, %1, %2, %3, %4, %5, %6, %7, %8, %9, %10, %11, %12, %13, %14, %15, %16, %17, %18, %19, %20, %21, %22, %23, %24, %25, %26, %27, %28, %29, %30, %31, %32, %33, %34, %35, %36, %37, %38, %39, %40, %41, %42, %43, %44, %45, %46, %47, %48, %49, %50, %51, %52, %53, %54, %55, %56, %57, %58, %59, %60, %61, %62, %63}, "
        "%64, %65, 1, 1, 1, 0, 1;\n"
        : "+f"(d[0]), "+f"(d[1]), "+f"(d[2]), "+f"(d[3]), "+f"(d[4]), "+f"(d[5]), "+f"(d[6]), "+f"(d[7]), "+f"(d[8]), "+f"(d[9]), "+f"(d[10]), "+f"(d[11]), "+f"(d[12]), "+f"(d[13]), "+f"(d[14]), "+f"(d[15]), "+f"(d[16]), "+f"(d[17]), "+f"(d[18]), "+f"(d[19]), "+f"(d[20]), "+f"(d[21]), "+f"(d[22]), "+f"(d[23]), "+f"(d[24]), "+f"(d[25]), "+f"(d[26]), "+f"(d[27]), "+f"(d[28]), "+f"(d[29]), "+f"(d[30]), "+f"(d[31]), "+f"(d[32]), "+f"(d[33]), "+f"(d[34]), "+f"(d[35]), "+f"(d[36]), "+f"(d[37]), "+f"(d[38]), "+f"(d[39]), "+f"(d[40]), "+f"(d[41]), "+f"(d[42]), "+f"(d[43]), "+f"(d[44]), "+f"(d[45]), "+f"(d[46]), "+f"(d[47]), "+f"(d[48]), "+f"(d[49]), "+f"(d[50]), "+f"(d[51]), "+f"(d[52]), "+f"(d[53]), "+f"(d[54]), "+f"(d[55]), "+f"(d[56]), "+f"(d[57]), "+f"(d[58]), "+f"(d[59]), "+f"(d[60]), "+f"(d[61]), "+f"(d[62]), "+f"(d[63])
        : "l"(da), "l"(db));
}

__device__ __forceinline__ uint4 quad_transpose(uint32_t v0, uint32_t v1, uint32_t v2, uint32_t v3, int j) {
    const bool o1 = j & 1, o2 = j & 2;
    uint32_t x0 = o1 ? v0 : v1, x1 = o1 ? v2 : v3;
    x0 = __shfl_xor_sync(~0u, x0, 1); x1 = __shfl_xor_sync(~0u, x1, 1);
    const uint32_t a0 = o1 ? x0 : v0, a1 = o1 ? v1 : x0, b0 = o1 ? x1 : v2, b1 = o1 ? v3 : x1;
    uint32_t y0 = o2 ? a0 : b0, y1 = o2 ? a1 : b1;
    y0 = __shfl_xor_sync(~0u, y0, 2); y1 = __shfl_xor_sync(~0u, y1, 2);
    return o2 ? make_uint4(y0, y1, b0, b1) : make_uint4(a0, a1, y0, y1);
}

constexpr float MEM_SCALE = 1.0f / 64.0f;
constexpr float SM_SCALE_LOG2 = 0.08838834764831845f * 1.4426950408889634f;
#define GATE9 1
#define WO_INFLIGHT 3
#define NEAR_STEP 61
#define BACKOFF 0
#define XS 64
#define XPM 1
#define XP_OFF(w, g) (16384 + (w) * 128 + (g) * 16)
#define TSC 1150
#define TS 1

__device__ __forceinline__ bool xch_read(int s, uint32_t rw, uint32_t ln, uint32_t sb, uint32_t delay) {
    const uint32_t w = rw * 2 + (ln >> 4), g = (ln >> 1) & 7, hf = ln & 1;
    const unsigned char* pa = g_xch + s * XCH_BYTES + w * (32 * XS) + g * XS + hf * 16;
    const unsigned char* pe = g_xch + s * XCH_BYTES + XP_OFF(w, g);
    const uint32_t dst = sb + C_MEM + (w * 64 + hf * 8 + g) * 16;
    const uint32_t s0 = hf ? 0x5410 : 0x3210, s1 = hf ? 0x7610 : 0x3210;
    mbar_wait(sb + BAR + MB_RED * 8, s & 1);
    const uint32_t t0 = (uint32_t)clock();
    uint2 tg;
    for (unsigned it = 0; (tg = lds64v(sb + C_TGT)).x != (uint32_t)s + 1; ++it) if (it > (1u << 24)) __trap();
    while ((int)(gtime32() - tg.y) < 0) { }
    while ((uint32_t)clock() - t0 < delay) { }
    for (unsigned it = 0;; ++it) {
        uint4 a[4], e;
#pragma unroll
        for (int i = 0; i < 4; i++) a[i] = ldv128(pa + i * (8 * XS));
        e = ldv128(pe);
        const uint32_t c = ((a[0].w & a[1].w & a[2].w & a[3].w) >> 16) & e.y, d = ((a[0].w | a[1].w | a[2].w | a[3].w) >> 16) | e.y;
        a[0].w = __byte_perm(a[0].w, e.x, s0); a[1].w = __byte_perm(a[1].w, e.x, s1);
        a[2].w = __byte_perm(a[2].w, e.z, s0); a[3].w = __byte_perm(a[3].w, e.z, s1);
#pragma unroll
        for (int i = 0; i < 4; i++) sts128(dst + i * 256, a[i]);
        if (__all_sync(~0u, !hf || (c == 0x5000u && d == 0x5000u))) return it == 0;
        if (it > (1u << 20)) __trap();
        if (BACKOFF) { const uint32_t t1 = (uint32_t)clock(); while ((uint32_t)clock() - t1 < BACKOFF) { } }
    }
}

__device__ __forceinline__ void softmax_frags(float (&s0)[4], float (&s1)[4], float (&s2)[4], uint32_t (&pb)[5]) {
    float m0 = fmaxf(fmaxf(fmaxf(s0[0], s0[2]), fmaxf(s1[0], s1[2])), s2[0]);
    float m1 = fmaxf(fmaxf(fmaxf(s0[1], s0[3]), fmaxf(s1[1], s1[3])), s2[1]);
#pragma unroll
    for (int o = 4; o <= 16; o <<= 1) {
        m0 = fmaxf(m0, __shfl_xor_sync(~0u, m0, o));
        m1 = fmaxf(m1, __shfl_xor_sync(~0u, m1, o));
    }
    const float c = SM_SCALE_LOG2, n0 = -m0 * c, n1 = -m1 * c;
    pb[0] = movm(pack_bf16(ex2(fmaf(s0[0], c, n0)), ex2(fmaf(s0[1], c, n1))));
    pb[1] = movm(pack_bf16(ex2(fmaf(s0[2], c, n0)), ex2(fmaf(s0[3], c, n1))));
    pb[2] = movm(pack_bf16(ex2(fmaf(s1[0], c, n0)), ex2(fmaf(s1[1], c, n1))));
    pb[3] = movm(pack_bf16(ex2(fmaf(s1[2], c, n0)), ex2(fmaf(s1[3], c, n1))));
    pb[4] = movm(pack_bf16(ex2(fmaf(s2[0], c, n0)), ex2(fmaf(s2[1], c, n1))));
}

#define PIN() do { if (__builtin_expect(p.zero != 0, 0)) { while (ld_volatile_u32(&g_flags[F_EXIT]) == 0x7fffffffu) { } } } while (0)
#define MMA4(d, a, b0, b1) mma(d, (a)[0], (a)[1], (a)[2], (a)[3], b0, b1)
#define MMA4H(d, a, b0, b1) mma_h(d, (a)[0], (a)[1], (a)[2], (a)[3], b0, b1)
#define LDSM4(a, addr) ldsm4((a)[0], (a)[1], (a)[2], (a)[3], addr)
#define LDSM4T(a, addr) ldsm4t((a)[0], (a)[1], (a)[2], (a)[3], addr)
#define ZERO4(a) do { (a)[0] = (a)[1] = (a)[2] = (a)[3] = 0.f; } while (0)
#define CVT4(a) do { (a)[0] = bf2h((a)[0]); (a)[1] = bf2h((a)[1]); (a)[2] = bf2h((a)[2]); (a)[3] = bf2h((a)[3]); } while (0)

__device__ __forceinline__ uint32_t wfrag_off(uint32_t ln, uint32_t w4) {
    return ((ln >> 4) * 8 + (ln & 7)) * 128 + (((w4 * 2 + ((ln >> 3) & 1)) ^ (ln & 7)) << 4);
}
__device__ __forceinline__ uint32_t pub_off(uint32_t ln, uint32_t w4, uint32_t rank) { return (rank * 64 + w4 * 16) * 16 + ln * 4; }

template <int HALF>
__device__ __forceinline__ void load_kf(uint32_t (&kf)[8][2][4], uint32_t kx, uint32_t ln, uint32_t rank) {
    const uint32_t mi = ln >> 3, r8 = ln & 7;
    const uint32_t ka = kx + ((mi & 1) * 8 + r8) * 256 + ((((mi >> 1) ^ r8) ^ (rank * 8)) << 4);
#pragma unroll
    for (int i = HALF * 4; i < HALF * 4 + 4; i++) {
        LDSM4(kf[i][0], ka ^ (i << 5));
        LDSM4(kf[i][1], (ka ^ (i << 5)) + 4096);
    }
}

__device__ __forceinline__ void publish_kvm(uint32_t sb, int s, uint32_t rank) {
    asm volatile("fence.proxy.async.shared::cta;" ::: "memory");
    asm volatile("cp.async.bulk.global.shared::cta.bulk_group [%0], [%1], 2048;"
                 :: "l"(g_kvm + (s * H_ + cluster_id()) * 4096 + rank * 2048), "r"(sb + C_SKM + rank * 2048) : "memory");
    asm volatile("cp.async.bulk.commit_group;" ::: "memory");
}

__device__ __forceinline__ void pair_reduce(const float (&give)[4], const float (&keep)[4], uint32_t wr, uint32_t rd, int barid, uint32_t& v0, uint32_t& v1) {
    sts128(wr, make_uint4(__float_as_uint(give[0]), __float_as_uint(give[1]), __float_as_uint(give[2]), __float_as_uint(give[3])));
    bar_sync(barid, 64);
    const uint4 o = lds128(rd);
    v0 = pack_bf16(64.f * (keep[0] + __uint_as_float(o.x)), 64.f * (keep[1] + __uint_as_float(o.y)));
    v1 = pack_bf16(64.f * (keep[2] + __uint_as_float(o.z)), 64.f * (keep[3] + __uint_as_float(o.w)));
}

__device__ __forceinline__ void chain_role(const Params& p, const uint32_t sb) {
    const uint32_t rank = cta_rank(), head = cluster_id();
    const int tid = threadIdx.x, lane = tid & 31;
    const uint32_t warp = __shfl_sync(~0u, tid >> 5, 0), wg = warp >> 2, w4 = warp & 3;
    const uint32_t bar = sb + BAR;
    if (tid == 0) {
        {
            const uint32_t t0 = (uint32_t)clock();
            while ((uint32_t)clock() - t0 < 1400) { }
        }
        const int ec = head * 128 + rank * 64;
        mbar_expect(bar + MB_W1 * 8, 65536 + 32768);
        for (int i = 0; i < 8; i++) tma2d(sb + C_WK + i * 8192, &p.tmWk, ec, i * 64, bar + MB_W1 * 8);
        for (int i = 0; i < 4; i++) tma2d(sb + C_WQ + i * 8192, &p.tmWq, ec, 256 + i * 64, bar + MB_W1 * 8);
        mbar_expect(bar + MB_W0 * 8, 32768 + 65536);
        for (int i = 0; i < 4; i++) tma2d(sb + C_STAGE + i * 8192, &p.tmWq, ec, i * 64, bar + MB_W0 * 8);
        for (int i = 0; i < 8; i++) tma2d(sb + C_WO + i * 8192, &p.tmWv, ec, i * 64, bar + MB_W0 * 8);
        mbar_expect(bar + MB_QKR * 8, 2048);
        mbar_expect(bar + MB_V * 8, 2048);
    }
    {
        uint4* z = reinterpret_cast<uint4*>(g_xch + (size_t)(head * 2 + rank) * XCH_BYTES);
        for (int i = tid; i < XCH_BYTES / 16; i += NTHREADS) z[i] = make_uint4(0, 0, 0, 0);
    }
    {
        mbar_wait(bar + MB_W1 * 8, 0);
        DBG(tid == 0, 40000 + blockIdx.x * 16 + 0, gtime());
        for (int i = tid; i < 6144; i += NTHREADS) {
            const uint32_t a = sb + (i < 4096 ? C_WK + i * 16 : C_WQ + (i - 4096) * 16);
            const uint4 v = lds128(a);
            sts128(a, make_uint4(bf2h(v.x), bf2h(v.y), bf2h(v.z), bf2h(v.w)));
        }
    }
    const bool dbgme = blockIdx.x == 10 && (tid & 127) == 96; (void)dbgme;

    if (wg == 0) {
        uint32_t wq[16][4], kf[8][2][4];
        mbar_wait(bar + MB_W0 * 8, 0);
#pragma unroll
        for (int i = 0; i < 16; i++) { LDSM4T(wq[i], sb + C_STAGE + i * 2048 + wfrag_off(lane, w4)); CVT4(wq[i]); }
        __syncthreads();
        cluster_sync_relaxed();
        DBG(tid == 0, 40000 + blockIdx.x * 16 + 1, gtime());
        uint32_t st = 0, sph = 0;
        for (int s = 0; s < NSEG; s++) {
            const uint32_t par = s & 1;
            const uint32_t ln = lane_id(), lo = ln * 16, mi = ln >> 3, r8 = ln & 7;
            const uint32_t rank = cta_rank(), rb = mapa(sb, rank ^ 1);
            const uint32_t w4 = __shfl_sync(~0u, tid_x() >> 5, 0);
            const uint32_t wk = sb + C_WK + wfrag_off(ln, w4);
            constexpr int AKD = 4;
            uint32_t ak[AKD][2][4];
#pragma unroll
            for (int i = 0; i < AKD; i++) { LDSM4T(ak[i][0], wk + i * 4096); LDSM4T(ak[i][1], wk + i * 4096 + 2048); }
            bar_sync(1, 192);
            uint32_t v0, v1;
            {
                float q0[4], q1[4], k0[4], k1[4];
                ZERO4(q0); ZERO4(q1); ZERO4(k0); ZERO4(k1);
                uint32_t b[2][4];
                LDSM4T(b[0], sb + C_MEM + lo);
#pragma unroll
                for (int k2 = 0; k2 < 8; k2++) {
                    if (k2 < 7) LDSM4T(b[(k2 + 1) & 1], sb + C_MEM + lo + (k2 + 1) * 512);
                    MMA4H(k0, ak[k2 % AKD][0], b[k2 & 1][0], b[k2 & 1][1]);
                    MMA4H(k1, ak[k2 % AKD][1], b[k2 & 1][2], b[k2 & 1][3]);
                    if (k2 + AKD < 8) { LDSM4T(ak[k2 % AKD][0], wk + (k2 + AKD) * 4096); LDSM4T(ak[k2 % AKD][1], wk + (k2 + AKD) * 4096 + 2048); }
                    MMA4H(q0, wq[2 * k2], b[k2 & 1][0], b[k2 & 1][1]);
                    MMA4H(q1, wq[2 * k2 + 1], b[k2 & 1][2], b[k2 & 1][3]);
                    if (k2 < 7) PIN();
                }
                bar_arrive(8, 384);
#pragma unroll
                for (int i = 0; i < 4; i++) { q0[i] += q1[i]; k0[i] += k1[i]; }
                pair_reduce(k0, q0, sb + C_XP + w4 * 1024 + lo, sb + C_XP + w4 * 1024 + 512 + lo, 4 + w4, v0, v1);
                const uint32_t po = C_SQ + pub_off(ln, w4, rank);
                st_async_b32(rb + po, v0, rb + BAR + MB_QKR * 8);
                st_async_b32(rb + po + 128, v1, rb + BAR + MB_QKR * 8);
                sts32(sb + po, v0);
                sts32(sb + po + 128, v1);
            }
            DBG0D(dbgme, s * 16 + 2, v1);
            const uint32_t skm = sb + C_SKM + lo, svm = sb + C_SVM + lo;
            const uint32_t vx = sb + C_KV + st * 16384 + 8192 + ((mi >> 1) * 8 + r8) * 256 + (((mi & 1) ^ r8) << 4);
            const uint32_t sq = sb + C_SQ + lo;
            const uint32_t own = rank * 1024, oth = own ^ 1024;
            const uint32_t ONE = 0x3F803F80u;
            if (s == 0) {
                mbar_wait(bar + MB_KV * 8, 0);
                DBG(tid == 0, 40000 + blockIdx.x * 16 + 2, gtime());
                load_kf<0>(kf, sb + C_KV, ln, rank);
            }
            bar_sync(2, 256);
            if (s == NSEG - 1) break;
            {
                float s0[4], s1[4], s2[4];
                ZERO4(s0); ZERO4(s1); ZERO4(s2);
                uint32_t q[2][4], m[2][4];
                LDSM4T(q[0], sq + own);
                LDSM4T(m[0], skm + own);
                LDSM4T(q[1], sq + own + 512);
                LDSM4T(m[1], skm + own + 512);
                PIN();
                load_kf<1>(kf, sb + C_KV + st * 16384, ln, rank);
                if (GATE9) bar_arrive(9, 256);
#pragma unroll
                for (int h2 = 0; h2 < 2; h2++) {
                    MMA4(s0, kf[2 * h2][0], q[h2][0], q[h2][1]);
                    MMA4(s1, kf[2 * h2][1], q[h2][0], q[h2][1]);
                    mma(s2, m[h2][0], 0u, m[h2][1], 0u, q[h2][0], q[h2][1]);
                    MMA4(s0, kf[2 * h2 + 1][0], q[h2][2], q[h2][3]);
                    MMA4(s1, kf[2 * h2 + 1][1], q[h2][2], q[h2][3]);
                    mma(s2, m[h2][2], 0u, m[h2][3], 0u, q[h2][2], q[h2][3]);
                }
                DBG0D(dbgme, s * 16 + 5, __float_as_uint(s2[0] + s1[0] + s0[0]));
                mbar_wait(bar + MB_QKR * 8, par);
                DBG0C(dbgme, s * 16 + 6, clock64());
                LDSM4T(q[0], sq + oth);
                LDSM4T(m[0], skm + oth);
                LDSM4T(q[1], sq + oth + 512);
                LDSM4T(m[1], skm + oth + 512);
                PIN();
                MMA4(s0, kf[4][0], q[0][0], q[0][1]);
                MMA4(s1, kf[4][1], q[0][0], q[0][1]);
                mma(s2, m[0][0], 0u, m[0][1], 0u, q[0][0], q[0][1]);
                MMA4(s0, kf[5][0], q[0][2], q[0][3]);
                MMA4(s1, kf[5][1], q[0][2], q[0][3]);
                mma(s2, m[0][2], 0u, m[0][3], 0u, q[0][2], q[0][3]);
                MMA4(s0, kf[6][0], q[1][0], q[1][1]);
                MMA4(s1, kf[6][1], q[1][0], q[1][1]);
                mma(s2, m[1][0], 0u, m[1][1], 0u, q[1][0], q[1][1]);
                MMA4(s0, kf[7][0], q[1][2], q[1][3]);
                MMA4(s1, kf[7][1], q[1][2], q[1][3]);
                mma(s2, m[1][2], 0u, m[1][3], 0u, q[1][2], q[1][3]);
                if (w4 == 0 && ln == 0) mbar_expect(bar + MB_QKR * 8, 2048);
                uint32_t vf[2][2][4];
#pragma unroll
                for (int e2 = 0; e2 < 2; e2++) {
                    LDSM4T(vf[e2][0], vx ^ ((w4 * 2 + e2) << 5));
                    LDSM4T(vf[e2][1], (vx ^ ((w4 * 2 + e2) << 5)) + 4096);
                }
                uint32_t pb[5];
                DBG0D(dbgme, s * 16 + 11, __float_as_uint(s0[0] + s1[0] + s2[0]));
                softmax_frags(s0, s1, s2, pb);
                DBG0D(dbgme, s * 16 + 12, pb[4] ^ pb[0]);
                float o0[4], o1[4], l[4];
                ZERO4(o0); ZERO4(o1); ZERO4(l);
                MMA4(o0, vf[0][0], pb[0], pb[1]);
                MMA4(o1, vf[1][0], pb[0], pb[1]);
                mma(l, ONE, ONE, ONE, ONE, pb[0], pb[1]);
                mbar_wait(bar + MB_V * 8, par);
                uint32_t vm[4];
                LDSM4(vm, svm + w4 * 512);
                MMA4(o0, vf[0][1], pb[2], pb[3]);
                MMA4(o1, vf[1][1], pb[2], pb[3]);
                mma(l, ONE, ONE, ONE, ONE, pb[2], pb[3]);
                mma(o0, vm[0], vm[1], 0u, 0u, pb[4], 0u);
                mma(o1, vm[2], vm[3], 0u, 0u, pb[4], 0u);
                mma(l, ONE, ONE, ONE, ONE, pb[4], 0u);
                const uint32_t so = sb + C_SO + w4 * 512 + ln * 4;
                sts32(so, pack_bf16(o0[0], o0[1]));
                sts32(so + 128, pack_bf16(o0[2], o0[3]));
                sts32(so + 256, pack_bf16(o1[0], o1[1]));
                sts32(so + 384, pack_bf16(o1[2], o1[3]));
                if (w4 == 0 && ln < 4) sts64(sb + C_SL + ln * 8, __float_as_uint(l[0]), __float_as_uint(l[1]));
                bar_arrive(3, 256);
                if (w4 == 0 && ln == 0) { mbar_expect(bar + MB_V * 8, 2048); publish_kvm(sb, s, rank); }
                __syncwarp();
                mbar_wait(bar + MB_RED * 8, par);
                if (s + 2 < NSEG) {
                    if (++st == 3) { st = 0; sph ^= 1; }
                    mbar_wait(bar + (MB_KV + st) * 8, sph);
                    load_kf<0>(kf, sb + C_KV + st * 16384, ln, rank);
                }
            }
            if (w4 == 0 && ln == 0) {
                if ((s & 3) == 3) {
                    asm volatile("cp.async.bulk.wait_group 0;" ::: "memory");
                    fence_proxy_async();
                    asm volatile("red.relaxed.gpu.global.add.u32 [%0], 1;" :: "l"(&g_flags[F_DONE + (s >> 2)]) : "memory");
                } else asm volatile("cp.async.bulk.wait_group.read 0;" ::: "memory");
            }
            __syncwarp();
        }
        mbar_wait(bar + MB_QKR * 8, 1);
        mbar_wait(bar + MB_V * 8, 1);
        if (tid == 0) {
            publish_kvm(sb, NSEG - 1, rank);
            asm volatile("cp.async.bulk.wait_group 0;" ::: "memory");
            fence_proxy_async();
            asm volatile("red.relaxed.gpu.global.add.u32 [%0], 1;" :: "l"(&g_flags[F_DONE + 15]) : "memory");
        }
        __syncwarp();
        __syncthreads();
    } else if (wg == 1) {
        {
            const int t2 = tid - 128;
            for (int i = t2; i < 8 * 512 / 2; i += 128) {
                const int tok = i >> 8, k = (i & 255) * 2;
                const uint32_t v = *reinterpret_cast<const uint32_t*>(p.mem0 + tok * 512 + k);
                const uint32_t w = pack_f16(bf_lo(v) * MEM_SCALE, bf_hi(v) * MEM_SCALE);
                asm volatile("st.shared.u16 [%0], %1;" :: "r"(sb + C_MEM + k * 16 + tok * 2), "h"((unsigned short)(w & 0xffff)) : "memory");
                asm volatile("st.shared.u16 [%0], %1;" :: "r"(sb + C_MEM + (k + 1) * 16 + tok * 2), "h"((unsigned short)(w >> 16)) : "memory");
            }
        }
        __syncthreads();
        cluster_sync_relaxed();
        uint32_t wa[32][4];
#pragma unroll
        for (int i = 0; i < 32; i++) LDSM4T(wa[i], sb + (i < 16 ? C_WQ + i * 2048 : C_WK + i * 2048) + wfrag_off(lane, w4));
        if (tid == 128) flag_wait(&g_flags[F_ZERO], 2 * NCHAIN);
        __syncwarp();
        mbar_wait(bar + MB_W2 * 8, 0);
        for (int s = 0; s < NSEG; s++) {
            const uint32_t par = s & 1;
            const uint32_t ln = lane_id(), lo = ln * 16, j = ln & 3;
            const uint32_t rank = cta_rank(), rb = mapa(sb, rank ^ 1), w4 = __shfl_sync(~0u, (tid_x() >> 5) & 3, 0);
            bar_sync(10, 192);
            DBGD(dbgme, s * 16 + 1, lds32(sb + C_MEM));
            uint32_t v0, v1;
            {
                float q0[4], q1[4], k0[4], k1[4];
                ZERO4(q0); ZERO4(q1); ZERO4(k0); ZERO4(k1);
                uint32_t b[2][4];
                LDSM4T(b[0], sb + C_MEM + 4096 + lo);
#pragma unroll
                for (int k2 = 0; k2 < 8; k2++) {
                    if (k2 < 7) LDSM4T(b[(k2 + 1) & 1], sb + C_MEM + 4096 + lo + (k2 + 1) * 512);
                    MMA4H(q0, wa[2 * k2], b[k2 & 1][0], b[k2 & 1][1]);
                    MMA4H(q1, wa[2 * k2 + 1], b[k2 & 1][2], b[k2 & 1][3]);
                    MMA4H(k0, wa[16 + 2 * k2], b[k2 & 1][0], b[k2 & 1][1]);
                    MMA4H(k1, wa[17 + 2 * k2], b[k2 & 1][2], b[k2 & 1][3]);
                    if (k2 < 7) PIN();
                }
                bar_arrive(8, 384);
#pragma unroll
                for (int i = 0; i < 4; i++) { q0[i] += q1[i]; k0[i] += k1[i]; }
                pair_reduce(q0, k0, sb + C_XP + w4 * 1024 + 512 + lo, sb + C_XP + w4 * 1024 + lo, 4 + w4, v0, v1);
                const uint32_t po = pub_off(ln, w4, rank);
                st_async_b32(rb + C_SKM + po, v0, rb + BAR + MB_QKR * 8);
                st_async_b32(rb + C_SKM + po + 128, v1, rb + BAR + MB_QKR * 8);
                sts32(sb + C_SKM + po, v0);
                sts32(sb + C_SKM + po + 128, v1);
                bar_arrive(2, 256);
                if (TS && w4 == 0 && ln == 0)
                    asm volatile("st.relaxed.gpu.global.u32 [%0], %1;"
                                 :: "l"(g_xch + s * XCH_BYTES + 20480 + blockIdx.x * 4), "r"(gtime32() | 1u) : "memory");
            }
            DBGD(dbgme, 1024 + s * 16 + 0, v1);
            if (s == NSEG - 1) break;
            {
                {
                    const uint32_t a = sb + C_WO + w4 * 16384 + wfrag_off(ln, 0), z = p.zero;
#pragma unroll
                    for (int i = 0; i < 32; i++) {
                        if (GATE9 && i == GATE9 - 1) bar_sync(9, 256);
                        const int ks = i >> 2, mt = i & 3, pi = i - (i < GATE9 ? 1 : WO_INFLIGHT), pk = pi >> 2, pm = pi & 3;
                        uint32_t ad = (a ^ (mt << 5)) + ks * 2048;
                        if (pi >= 0) ad += wa[pm * 8 + pk][3] & z;
                        LDSM4T(wa[mt * 8 + ks], ad);
                    }
                }
                unsigned char* xb = g_xch + s * XCH_BYTES + (rank * 4 + w4) * (32 * XS) + (ln >> 2) * XS + (j & 1) * 16 + (j >> 1) * 8;
                unsigned char* xe = g_xch + s * XCH_BYTES + XP_OFF(rank * 4 + w4, ln >> 2);
                asm volatile("" : "+l"(xb), "+l"(xe));
                DBGD(dbgme, 1024 + s * 16 + 1, wa[31][3]);
                bar_sync(3, 256);
                DBGD(dbgme, 1024 + s * 16 + 4, lds32(sb + C_SO));
                float acc[4][4];
#pragma unroll
                for (int i = 0; i < 4; i++) ZERO4(acc[i]);
                uint32_t b[4][4];
#pragma unroll
                for (int k2 = 0; k2 < 4; k2++) LDSM4T(b[k2], sb + C_SO + lo + k2 * 512);
                const float r0 = __fdividef(MEM_SCALE, __uint_as_float(lds32(sb + C_SL + j * 8)));
                const float r1 = __fdividef(MEM_SCALE, __uint_as_float(lds32(sb + C_SL + j * 8 + 4)));
#pragma unroll
                for (int k2 = 0; k2 < 4; k2++) {
#pragma unroll
                    for (int mt = 0; mt < 4; mt++) MMA4(acc[mt], wa[mt * 8 + 2 * k2], b[k2][0], b[k2][1]);
#pragma unroll
                    for (int mt = 0; mt < 4; mt++) MMA4(acc[mt], wa[mt * 8 + 2 * k2 + 1], b[k2][2], b[k2][3]);
                }
#pragma unroll
                for (int mt = 0; mt < 4; mt++) {
                    const uint32_t x = pack_f16(acc[mt][0] * r0, acc[mt][1] * r1);
                    const uint32_t y = pack_f16(acc[mt][2] * r0, j == 3 ? 1.0f : acc[mt][3] * r1);
                    const uint32_t o = __shfl_xor_sync(~0u, (j & 1) ? x : y, 1);
                    asm volatile("red.relaxed.gpu.global.add.noftz.v2.f16x2 [%0], {%1, %2};"
                                 :: "l"(xb + mt * (8 * XS)), "r"((j & 1) ? o : x), "r"((j & 1) ? y : o) : "memory");
                }
                {
                    const uint32_t e0 = pack_f16(acc[0][3] * r1, acc[1][3] * r1);
                    const uint32_t e1 = pack_f16(acc[2][3] * r1, acc[3][3] * r1);
                    asm volatile("{\n.reg .pred p;\nsetp.eq.u32 p, %4, 3;\n@p red.relaxed.gpu.global.add.noftz.v4.f16x2 [%0], {%1, %2, %3, %2};\n}"
                                 :: "l"(xe), "r"(e0), "r"(0x00003C00u), "r"(e1), "r"(j) : "memory");
                }
                if (ln == 0) mbar_arrive(bar + MB_RED * 8);
                DBGC(dbgme, 1024 + s * 16 + 2, clock64());
                const uint32_t a = sb + wfrag_off(ln, w4), z = p.zero;
#pragma unroll
                for (int i = 0; i < 32; i++) LDSM4T(wa[i], a + (i < 16 ? C_WQ : C_WK) + i * 2048 + (i >= 2 ? wa[i >= 2 ? i - 2 : 0][3] & z : 0u));
                DBGD(dbgme, 1024 + s * 16 + 3, wa[31][3]);
            }
        }
        __syncthreads();
    } else {
        uint32_t wv[32][4];
        mbar_wait(bar + MB_W0 * 8, 0);
#pragma unroll
        for (int i = 0; i < 32; i++) { LDSM4T(wv[i], sb + C_WO + i * 2048 + wfrag_off(lane, w4)); CVT4(wv[i]); if ((i & 3) == 3) PIN(); }
        __syncthreads();
        if (tid == 256) {
            mbar_expect(bar + MB_W2 * 8, 65536);
            for (int i = 0; i < 8; i++) tma2d(sb + C_WO + i * 8192, &p.tmWo, rank * 256 + (i >> 1) * 64, head * 128 + (i & 1) * 64, bar + MB_W2 * 8);
        }
        if (tid == 320) flag_signal(&g_flags[F_ZERO]);
        __syncwarp();
        cluster_sync_relaxed();
        int ready = 0;
        uint32_t dly = 800;
        uint32_t st = 2;
        bar_arrive(w4 < 2 ? 1 : 10, 192);
        for (int s = 0; s < NSEG; s++) {
            const uint32_t par = s & 1;
            const uint32_t ln = lane_id();
            const uint32_t rank = cta_rank(), head = cluster_id(), rb = mapa(sb, rank ^ 1), lb = mapa(sb, rank);
            const uint32_t w4 = __shfl_sync(~0u, (tid_x() >> 5) & 3, 0);
            const unsigned char* qkv_h = reinterpret_cast<const unsigned char*>(g_qkv) + (size_t)head * 16384;
            {
                float a0[4], a1[4];
                ZERO4(a0); ZERO4(a1);
                uint32_t b[4][4];
                const uint32_t ml = sb + C_MEM + ln * 16;
                bar_sync(8, 384);
#pragma unroll
                for (int i = 0; i < 3; i++) LDSM4T(b[i], ml + i * 512);
                DBG(dbgme, 3072 + s, clock64());
                DBG(tid == 256 && s < 3, 40000 + blockIdx.x * 16 + 3 + s, gtime());
#pragma unroll
                for (int k2 = 0; k2 < 16; k2++) {
                    if (k2 + 3 < 16) LDSM4T(b[(k2 + 3) & 3], ml + (k2 + 3) * 512);
                    MMA4H(a0, wv[2 * k2], b[k2 & 3][0], b[k2 & 3][1]);
                    MMA4H(a1, wv[2 * k2 + 1], b[k2 & 3][2], b[k2 & 3][3]);
                    if (k2 < 13) PIN();
                }
                const uint32_t v0 = pack_bf16(64.f * (a0[0] + a1[0]), 64.f * (a0[1] + a1[1]));
                const uint32_t v1 = pack_bf16(64.f * (a0[2] + a1[2]), 64.f * (a0[3] + a1[3]));
                const uint32_t po = pub_off(ln, w4, rank);
                st_async_b32(rb + C_SVM + po, v0, rb + BAR + MB_V * 8);
                st_async_b32(rb + C_SVM + po + 128, v1, rb + BAR + MB_V * 8);
                st_async_b32(lb + C_SVM + po, v0, lb + BAR + MB_V * 8);
                st_async_b32(lb + C_SVM + po + 128, v1, lb + BAR + MB_V * 8);
                DBGD(dbgme, 2048 + s * 16 + 0, v1);
            }
            if (s == NEAR_STEP && blockIdx.x == 0 && w4 == 0 && ln == 0) asm volatile("st.relaxed.gpu.global.u32 [%0], 1;" :: "l"(&g_flags[F_NEAR]) : "memory");
            if (w4 == 3 && ln < 3 && s + 3 < NSEG - 1 && blockIdx.x * 3 + ln < XCH_BYTES / 128)
                asm volatile("prefetch.global.L2 [%0];" :: "l"(g_xch + (s + 3) * XCH_BYTES + (blockIdx.x * 3 + ln) * 128));
            if (w4 == 1 && s == 0) {
                flag_wait(&g_flags[F_QKV + head], 2);
                if (elect_one()) {
                    mbar_expect(bar + MB_KV * 8, 16384);
                    bulk_g2s(sb + C_KV, qkv_h, 16384, bar + MB_KV * 8);
                    mbar_expect(bar + MB_KV1 * 8, 16384);
                    bulk_g2s(sb + C_KV + 16384, qkv_h + H_ * 16384, 16384, bar + MB_KV1 * 8);
                }
                __syncwarp();
            }
            if (w4 == 1 && s + 3 < NSEG) {
                const int n = s + 2;
                if ((n >> 1) > ready) {
                    ready = n >> 1;
                    flag_wait(&g_flags[F_QKV + ready * 32 + head], 2);
                }
                if (elect_one()) {
                    mbar_expect(bar + (MB_KV + st) * 8, 16384);
                    bulk_g2s(sb + C_KV + st * 16384, qkv_h + (size_t)(n) * (H_ * 16384), 16384, bar + (MB_KV + st) * 8);
                }
                if (++st == 3) st = 0;
                if (ready < 31 && ready < (n >> 1) + 2) {
                    const int far = ready + 4 < 32 ? ready + 4 : 31;
                    const uint32_t f0 = ld_volatile_u32(&g_flags[F_QKV + far * 32 + head]), f1 = ld_volatile_u32(&g_flags[F_QKV + (ready + 1) * 32 + head]);
                    ready = __shfl_sync(~0u, f0 >= 2 ? far : f1 >= 2 ? ready + 1 : ready, 0);
                    asm volatile("fence.acquire.gpu;" ::: "memory");
                    fence_proxy_async();
                }
            }
            __syncwarp();
            DBGC(blockIdx.x == 10 && lane == 0 && w4 < 2, 2048 + s * 16 + 1 + w4, clock64());
            if (s < NSEG - 1) {
                if (TS && w4 == 2) {
                    const uint32_t now = gtime32();
                    uint2 t;
                    for (unsigned it = 0;; ++it) {
                        t = ldv64(g_xch + s * XCH_BYTES + 20480 + ln * 8);
                        if (__all_sync(~0u, t.x & t.y & 1)) break;
                        if (it > (1u << 20)) __trap();
                    }
                    const int late = __reduce_max_sync(~0u, max((int)(t.x - now), (int)(t.y - now)));
                    if (ln == 0) sts64(sb + C_TGT, s + 1, now + late + TSC);
                }
                const bool hit = xch_read(s, w4, ln, sb, dly);
                dly = hit ? max(dly - ((uint32_t)p.delay >> 24), (uint32_t)p.delay & 0xfff) : min(dly + ((p.delay >> 12) & 0xfff), 1400u);
                bar_arrive(w4 < 2 ? 1 : 10, 192);
            }
        }
        __syncthreads();
    }
    cluster_sync_relaxed();
}

#define RESV_MASK 0xffffu

__device__ __forceinline__ float warp_sum(float v) {
#pragma unroll
    for (int o = 16; o >= 1; o >>= 1) v += __shfl_xor_sync(~0u, v, o);
    return v;
}

__device__ __forceinline__ void mod_job(const Params& p, const uint32_t sb, const int job, const int ct, const bool sig) {
    const int warp = ct >> 5, lane = ct & 31, chunk = ct & 7, rg = ct >> 3;
    float a[8] = {0.f, 0.f, 0.f, 0.f, 0.f, 0.f, 0.f, 0.f};
    uint4 w[16]; float cs[16];
#pragma unroll
    for (int i = 0; i < 16; i++) {
        const int row = i * 32 + rg;
        w[i] = __ldg(reinterpret_cast<const uint4*>(p.wmod + (size_t)row * 3072 + job * 64 + chunk * 8));
        cs[i] = __bfloat162float(p.c[row]);
    }
    if (sig && ct == 224) mbar_arrive(sb + BAR + MB_P0 * 8);
    DBG(ct == 0 && cs[0] != 1.2345f, 40000 + blockIdx.x * 16 + 11, gtime());
    DBG(ct == 0 && w[0].x != 0x12345, 40000 + blockIdx.x * 16 + 12, gtime());
    DBG(ct == 0 && w[15].x != 0x12345, 40000 + blockIdx.x * 16 + 13, gtime());
#pragma unroll
    for (int i = 0; i < 16; i++) {
        const float sv = bf_round(__fdividef(cs[i], 1.f + __expf(-cs[i])));
        a[0] = fmaf(sv, bf_lo(w[i].x), a[0]); a[1] = fmaf(sv, bf_hi(w[i].x), a[1]);
        a[2] = fmaf(sv, bf_lo(w[i].y), a[2]); a[3] = fmaf(sv, bf_hi(w[i].y), a[3]);
        a[4] = fmaf(sv, bf_lo(w[i].z), a[4]); a[5] = fmaf(sv, bf_hi(w[i].z), a[5]);
        a[6] = fmaf(sv, bf_lo(w[i].w), a[6]); a[7] = fmaf(sv, bf_hi(w[i].w), a[7]);
    }
    DBG(ct == 0 && a[0] != 1.2345f, 40000 + blockIdx.x * 16 + 10, gtime());
#pragma unroll
    for (int i = 0; i < 8; i++) { a[i] += __shfl_xor_sync(~0u, a[i], 8); a[i] += __shfl_xor_sync(~0u, a[i], 16); }
    const uint32_t red = sb + W_GB;
    if (lane < 8) {
#pragma unroll
        for (int i = 0; i < 8; i++) sts32(red + (warp * 64 + lane * 8 + i) * 4, __float_as_uint(a[i]));
    }
    bar_sync(5, 256);
    if (ct < 64) {
        float t = 0.f;
#pragma unroll
        for (int i = 0; i < 8; i++) t += __uint_as_float(lds32(red + (i * 64 + ct) * 4));
        asm volatile("st.relaxed.gpu.global.u32 [%0], %1;" :: "l"(g_mod + job * 64 + ct), "r"(__float_as_uint(bf_round(t)) | 1u) : "memory");
    }
    bar_sync(5, 256);
    DBG(ct == 0, 40000 + blockIdx.x * 16 + 0, gtime());
    if (ct == 32) flag_signal(&g_flags[F_MOD]);
}

__device__ __forceinline__ void phase0(const Params& p, const uint32_t sb, const int widx, const int nworkers, const int ct) {
    const int warp = ct >> 5, lane = ct & 31;
    bool first = true;
    DBG(ct == 0, 40000 + blockIdx.x * 16 + 9, gtime());
    for (int job = widx; job < 64 || first; job += nworkers) {
        uint4 xv[4][2];
        if (job < 64) {
#pragma unroll
            for (int r = 0; r < 4; r++)
#pragma unroll
                for (int hh = 0; hh < 2; hh++)
                    xv[r][hh] = __ldg(reinterpret_cast<const uint4*>(p.x + (size_t)(job * 32 + warp * 4 + r) * D_ + hh * 256 + lane * 8));
        }
        if (first) {
            const int m0 = widx >= 4 ? widx - 4 : widx - 4 + nworkers;
            if (m0 >= 16 && ct == 224) mbar_arrive(sb + BAR + MB_P0 * 8);
            for (int mj = m0; mj < 16; mj += nworkers) mod_job(p, sb, mj, ct, mj == m0);
        }
        if (job >= 64) break;
        float v[4][16], mean[4], rstd[4];
#pragma unroll
        for (int r = 0; r < 4; r++) {
#pragma unroll
            for (int hh = 0; hh < 2; hh++) {
                const uint4 u = xv[r][hh];
                v[r][hh * 8 + 0] = bf_lo(u.x); v[r][hh * 8 + 1] = bf_hi(u.x); v[r][hh * 8 + 2] = bf_lo(u.y); v[r][hh * 8 + 3] = bf_hi(u.y);
                v[r][hh * 8 + 4] = bf_lo(u.z); v[r][hh * 8 + 5] = bf_hi(u.z); v[r][hh * 8 + 6] = bf_lo(u.w); v[r][hh * 8 + 7] = bf_hi(u.w);
            }
            float sum = 0.f;
#pragma unroll
            for (int i = 0; i < 16; i++) sum += v[r][i];
            mean[r] = warp_sum(sum) * (1.f / D_);
            float sq = 0.f;
#pragma unroll
            for (int i = 0; i < 16; i++) { const float d = v[r][i] - mean[r]; sq = fmaf(d, d, sq); }
            rstd[r] = rsqrtf(warp_sum(sq) * (1.f / D_) + 1e-5f);
        }
        first = false;
#pragma unroll 1
        for (int real = 1; real < 2; real++) {
        if (warp < 2 && real) {
            uint4 a[2], b[2];
            for (unsigned it = 0;; ++it) {
#pragma unroll
                for (int i = 0; i < 2; i++) { a[i] = ldv128(g_mod + ct * 8 + i * 4); b[i] = ldv128(g_mod + 512 + ct * 8 + i * 4); }
                if (__all_sync(~0u, a[0].x & a[0].y & a[0].z & a[0].w & a[1].x & a[1].y & a[1].z & a[1].w &
                                    b[0].x & b[0].y & b[0].z & b[0].w & b[1].x & b[1].y & b[1].z & b[1].w & 1)) break;
                if (it > (1u << 22)) __trap();
                __nanosleep(100);
            }
#pragma unroll
            for (int i = 0; i < 2; i++)
                sts128(sb + W_GB + ct * 32 + i * 16, make_uint4(pack_bf16(bf_hi(a[i].x), 1.f + bf_hi(b[i].x)), pack_bf16(bf_hi(a[i].y), 1.f + bf_hi(b[i].y)),
                                                                pack_bf16(bf_hi(a[i].z), 1.f + bf_hi(b[i].z)), pack_bf16(bf_hi(a[i].w), 1.f + bf_hi(b[i].w))));
        }
        bar_sync(5, 256);
        DBG(ct == 0, 40000 + blockIdx.x * 16 + 2, gtime());
        float sh[16], sc[16];
#pragma unroll
        for (int i = 0; i < 4; i++) {
            const uint4 v = lds128(sb + W_GB + (i >> 1) * 1024 + lane * 32 + (i & 1) * 16);
            sh[i * 4 + 0] = bf_lo(v.x); sh[i * 4 + 1] = bf_lo(v.y); sh[i * 4 + 2] = bf_lo(v.z); sh[i * 4 + 3] = bf_lo(v.w);
            sc[i * 4 + 0] = bf_hi(v.x); sc[i * 4 + 1] = bf_hi(v.y); sc[i * 4 + 2] = bf_hi(v.z); sc[i * 4 + 3] = bf_hi(v.w);
        }
#pragma unroll
        for (int r = 0; r < 4; r++) {
            const int row = job * 32 + warp * 4 + r;
            unsigned char* hr = reinterpret_cast<unsigned char*>(g_h) + (size_t)(row >> 6) * 65536 + (row & 63) * 64 + (lane >> 2) * 4096 + (((lane & 3) ^ ((row >> 1) & 3)) << 4);
#pragma unroll
            for (int hh = 0; hh < 2; hh++) {
                float o[8];
#pragma unroll
                for (int i = 0; i < 8; i++) o[i] = fmaf((v[r][hh * 8 + i] - mean[r]) * rstd[r], sc[hh * 8 + i], sh[hh * 8 + i]);
                if (real) *reinterpret_cast<uint4*>(hr + hh * 32768) =
                    make_uint4(pack_bf16(o[0], o[1]), pack_bf16(o[2], o[3]), pack_bf16(o[4], o[5]), pack_bf16(o[6], o[7]));
            }
        }
        }
        bar_sync(5, 256);
        if (ct == 0) {
            flag_signal(&g_flags[F_H + (job >> 1)]);
            asm volatile("red.relaxed.gpu.global.add.u32 [%0], 1;" :: "l"(&g_flags[F_HALL]) : "memory");
        }
        DBG(ct == 0, 40000 + blockIdx.x * 16 + 3, gtime());
    }
    const int spare = nworkers < 4 ? nworkers : 4;
    if (widx >= nworkers - spare) for (int mj = 16 + widx - (nworkers - spare); mj < 48; mj += spare) mod_job(p, sb, mj, ct, false);
}

__device__ __forceinline__ float gelu_tanh(float x) {
    const float u = 0.7978845608028654f * fmaf(0.044715f * x * x, x, x);
    float t; asm("tanh.approx.f32 %0, %1;" : "=f"(t) : "f"(u));
    return 0.5f * x * (1.f + t);
}

__device__ __forceinline__ void row_task(const Params& p, const uint32_t st, const bool ln, const int nsum, const int rs, const int r0,
                                         const int row0, const int lane, const float4 (&md)[12], const bool store) {
#pragma unroll 1
    for (int r = r0; r < rs; r += 2) {
        float4 a[4];
#pragma unroll
        for (int i = 0; i < 4; i++) a[i] = make_float4(0.f, 0.f, 0.f, 0.f);
        const uint32_t ra = st + r * 1024 + lane * 8;
#pragma unroll 1
        for (int q = 0; q < nsum; q++) {
#pragma unroll
            for (int i = 0; i < 4; i++) {
                const uint2 v = lds64v(ra + q * rs * 1024 + i * 256);
                a[i].x += bf_lo(v.x); a[i].y += bf_hi(v.x); a[i].z += bf_lo(v.y); a[i].w += bf_hi(v.y);
            }
        }
        const size_t ro = (size_t)(row0 + r) * D_ + lane * 4;
        float sum = 0.f;
#pragma unroll
        for (int i = 0; i < 4; i++) {
            float4 x;
            if (ln) {
                const uint2 v = lds64v(ra + nsum * rs * 1024 + i * 256);
                x = make_float4(bf_lo(v.x), bf_hi(v.x), bf_lo(v.y), bf_hi(v.y));
            } else {
                const uint4 v = lds128(st + nsum * rs * 1024 + r * 2048 + lane * 16 + i * 512);
                x = make_float4(__uint_as_float(v.x), __uint_as_float(v.y), __uint_as_float(v.z), __uint_as_float(v.w));
            }
            a[i].x = fmaf(md[i].x, a[i].x, x.x); a[i].y = fmaf(md[i].y, a[i].y, x.y);
            a[i].z = fmaf(md[i].z, a[i].z, x.z); a[i].w = fmaf(md[i].w, a[i].w, x.w);
            sum += (a[i].x + a[i].y) + (a[i].z + a[i].w);
        }
        if (ln) {
            const float mean = warp_sum(sum) * (1.f / D_);
            float sq = 0.f;
#pragma unroll
            for (int i = 0; i < 4; i++) {
                if (store) *reinterpret_cast<float4*>(g_x1 + ro + i * 128) = a[i];
                a[i].x -= mean; a[i].y -= mean; a[i].z -= mean; a[i].w -= mean;
                sq += (a[i].x * a[i].x + a[i].y * a[i].y) + (a[i].z * a[i].z + a[i].w * a[i].w);
            }
            const float rstd = rsqrtf(warp_sum(sq) * (1.f / D_) + 1e-5f);
#pragma unroll
            for (int i = 0; i < 4; i++) {
                a[i].x = fmaf(a[i].x * rstd, bf_round(1.f + md[8 + i].x), md[4 + i].x); a[i].y = fmaf(a[i].y * rstd, bf_round(1.f + md[8 + i].y), md[4 + i].y);
                a[i].z = fmaf(a[i].z * rstd, bf_round(1.f + md[8 + i].z), md[4 + i].z); a[i].w = fmaf(a[i].w * rstd, bf_round(1.f + md[8 + i].w), md[4 + i].w);
            }
        }
        bf16* dst = (ln ? g_h2 : p.out) + ro;
#pragma unroll
        for (int i = 0; i < 4; i++)
            if (store) *reinterpret_cast<uint2*>(dst + i * 128) = make_uint2(pack_bf16(a[i].x, a[i].y), pack_bf16(a[i].z, a[i].w));
    }
}

__device__ __forceinline__ void attend(const uint32_t (&q)[8][4], const uint32_t kv, const uint32_t km, const int mt, const int lane, bf16* og,
                                       const uint32_t af, const uint32_t ph, const bool real) {
    const int mi = lane >> 3, r8 = lane & 7, g = lane >> 2, j = lane & 3;
    float sc[5][4];
#pragma unroll
    for (int i = 0; i < 5; i++) ZERO4(sc[i]);
    const uint32_t ka = kv + r8 * 256 + ((mi ^ r8) << 4);
    const uint32_t va = kv + 8192 + ((mi & 1) * 8 + r8) * 256 + (((mi >> 1) ^ r8) << 4);
    if (real) mbar_wait(af, ph);
#pragma unroll
    for (int k2 = 0; k2 < 4; k2++) {
        uint32_t f[5][4];
        LDSM4T(f[4], km + k2 * 512 + lane * 16);
#pragma unroll
        for (int nt = 0; nt < 4; nt++) LDSM4(f[nt], (ka ^ (k2 << 6)) + nt * 2048);
#pragma unroll
        for (int nt = 0; nt < 5; nt++) MMA4(sc[nt], q[2 * k2], f[nt][0], f[nt][1]);
#pragma unroll
        for (int nt = 0; nt < 5; nt++) MMA4(sc[nt], q[2 * k2 + 1], f[nt][2], f[nt][3]);
    }
    __syncwarp();
    if (lane == 0 && real) mbar_arrive(af + (MB_AE - MB_AF) * 8);
    const int q0 = mt * 16 + g - 2 * j;
    float m0 = fmaxf(sc[4][0], sc[4][1]), m1 = fmaxf(sc[4][2], sc[4][3]);
#pragma unroll
    for (int nt = 0; nt < 4; nt++) {
        if (nt * 8 > q0) sc[nt][0] = -INFINITY;
        if (nt * 8 + 1 > q0) sc[nt][1] = -INFINITY;
        if (nt * 8 - 8 > q0) sc[nt][2] = -INFINITY;
        if (nt * 8 - 7 > q0) sc[nt][3] = -INFINITY;
        m0 = fmaxf(m0, fmaxf(sc[nt][0], sc[nt][1])); m1 = fmaxf(m1, fmaxf(sc[nt][2], sc[nt][3]));
    }
    m0 = fmaxf(m0, __shfl_xor_sync(~0u, m0, 1)); m1 = fmaxf(m1, __shfl_xor_sync(~0u, m1, 1));
    m0 = fmaxf(m0, __shfl_xor_sync(~0u, m0, 2)); m1 = fmaxf(m1, __shfl_xor_sync(~0u, m1, 2));
    const float c = SM_SCALE_LOG2, n0 = -m0 * c, n1 = -m1 * c;
    uint32_t pa[5][2];
#pragma unroll
    for (int nt = 0; nt < 5; nt++) {
        pa[nt][0] = pack_bf16(ex2(fmaf(sc[nt][0], c, n0)), ex2(fmaf(sc[nt][1], c, n0)));
        pa[nt][1] = pack_bf16(ex2(fmaf(sc[nt][2], c, n1)), ex2(fmaf(sc[nt][3], c, n1)));
    }
    float l[4];
    ZERO4(l);
    const uint32_t ONE = 0x3F803F80u;
    mma(l, pa[4][0], pa[4][1], 0u, 0u, ONE, 0u);
    mma(l, pa[0][0], pa[0][1], pa[1][0], pa[1][1], ONE, ONE);
    mma(l, pa[2][0], pa[2][1], pa[3][0], pa[3][1], ONE, ONE);
    const float r0 = __fdividef(1.f, l[0]), r1 = __fdividef(1.f, l[2]);
    bf16* d0 = og + (size_t)(mt * 16 + g) * 4096 + j * 8;
    if (real) mbar_wait(af + 8, ph);
#pragma unroll 1
    for (int c8 = 0; c8 < 2; c8++) {
        uint32_t vm[2][4], v[2][4][4];
        float o[2][4][4];
#pragma unroll
        for (int h = 0; h < 2; h++) {
            const int c4 = c8 * 2 + h;
            LDSM4(vm[h], km + 2048 + c4 * 512 + lane * 16);
            LDSM4T(v[h][0], va ^ (c4 << 6)); LDSM4T(v[h][1], va ^ ((c4 << 6) | 32));
            LDSM4T(v[h][2], (va ^ (c4 << 6)) + 4096); LDSM4T(v[h][3], (va ^ ((c4 << 6) | 32)) + 4096);
        }
#pragma unroll
        for (int i = 0; i < 8; i++) { ZERO4(o[i >> 2][i & 3]); mma(o[i >> 2][i & 3], pa[4][0], pa[4][1], 0u, 0u, vm[i >> 2][i & 3], 0u); }
#pragma unroll
        for (int i = 0; i < 8; i++)
            mma(o[i >> 2][i & 3], pa[0][0], pa[0][1], pa[1][0], pa[1][1], v[i >> 2][(i >> 1) & 1][(i & 1) * 2], v[i >> 2][(i >> 1) & 1][(i & 1) * 2 + 1]);
        if (mt) {
#pragma unroll
            for (int i = 0; i < 8; i++)
                mma(o[i >> 2][i & 3], pa[2][0], pa[2][1], pa[3][0], pa[3][1], v[i >> 2][2 + ((i >> 1) & 1)][(i & 1) * 2], v[i >> 2][2 + ((i >> 1) & 1)][(i & 1) * 2 + 1]);
        }
        uint4 w[4];
#pragma unroll
        for (int i = 0; i < 4; i++) {
            const int h = i >> 1, u = (i & 1) * 2;
            const float r = (i & 1) ? r1 : r0;
            w[i] = quad_transpose(pack_bf16(o[h][0][u] * r, o[h][0][u + 1] * r), pack_bf16(o[h][1][u] * r, o[h][1][u + 1] * r),
                                  pack_bf16(o[h][2][u] * r, o[h][2][u + 1] * r), pack_bf16(o[h][3][u] * r, o[h][3][u + 1] * r), j);
        }
        if (c8 == 1 && lane == 0 && real) mbar_arrive(af + (MB_AE - MB_AF + 1) * 8);
        if (real) {
#pragma unroll
            for (int i = 0; i < 4; i++) *reinterpret_cast<uint4*>(d0 + (i & 1) * 8 * 4096 + (c8 * 2 + (i >> 1)) * 32) = w[i];
        }
    }
}

__device__ __forceinline__ int gemm_nk(const Params& p, int type, int b) { return type == T_FFN1 ? 8 : type == T_WO ? 64 / p.sk1[b] : 28 / p.sk2[b]; }

template <int N>
__device__ __forceinline__ void gemm_task(const uint32_t sb, const uint32_t i2, const int nk, const int type, const int idx, const int row,
                                          const uint32_t rank, const int wgi, const int j, const bool elect, const uint32_t e2_rem, const uint32_t t) {
    const uint32_t bar = sb + BAR;
#pragma unroll 1
    for (int real = (N == 128 && (t >> 12)) ? 0 : 1; real < 2; real++) {
        float acc[N / 2];
#pragma unroll
        for (int i = 0; i < N / 2; i++) acc[i] = 0.f;
#pragma unroll 1
        for (int k = 0; k < nk * real; k++) {
            const uint32_t ii = i2 + k, slot = ii & 3, st = sb + slot * STAGE2;
            mbar_wait(bar + (MB_F2 + slot) * 8, (ii >> 2) & 1);
            wg_fence();
#pragma unroll
            for (int kk = 0; kk < 4; kk++) {
                const uint64_t da = gmma_desc(st + wgi * 8192 + kk * 32, 16, 1024, 1), db = gmma_desc(st + 16384 + kk * 2048, 8192, 1024, 1);
                if constexpr (N == 256) wgmma_n256(acc, da, db); else wgmma_n128(acc, da, db);
            }
            wg_commit();
            wg_wait<0>();
            if (elect) { mbar_arrive(bar + (MB_E2 + slot) * 8); mbar_arrive_remote(e2_rem + slot * 8); }
            __syncwarp();
        }
        DBG(threadIdx.x == 128 && rank == 0, 8192 + (t & 4095) * 4 + 1, gtime());
        if (type == T_FFN1) {
#pragma unroll
            for (int u = 0; u < 2; u++) {
                bf16* dst = g_act + (size_t)(row + u * 8) * F_ + idx * N + rank * (N / 2) + j * 8;
#pragma unroll
                for (int m = 0; m < N / 64; m++) {
                    uint32_t v[4];
#pragma unroll
                    for (int i = 0; i < 4; i++) {
                        const int a = (m * 4 + i) * 4 + u * 2;
                        v[i] = pack_bf16(gelu_tanh(acc[a]) * acc[N / 4 + a], gelu_tanh(acc[a + 1]) * acc[N / 4 + a + 1]);
                    }
                    const uint4 w = quad_transpose(v[0], v[1], v[2], v[3], j);
                    if (real) *reinterpret_cast<uint4*>(dst + m * 32) = w;
                }
            }
        } else {
            const int ks = N == 256 ? idx : idx >> 1, col = N == 256 ? rank * 256 : (idx & 1) * 256 + rank * 128;
            bf16* dst = (type == T_WO ? g_p1 : g_p2) + (size_t)ks * S_ * D_ + (size_t)row * D_ + col + j * 8;
#pragma unroll
            for (int u = 0; u < 2; u++)
#pragma unroll
                for (int m = 0; m < N / 32; m++) {
                    const int a = m * 16 + u * 2;
                    const uint4 w = quad_transpose(pack_bf16(acc[a], acc[a + 1]), pack_bf16(acc[a + 4], acc[a + 5]),
                                                   pack_bf16(acc[a + 8], acc[a + 9]), pack_bf16(acc[a + 12], acc[a + 13]), j);
                    if (real) *reinterpret_cast<uint4*>(dst + u * 8 * D_ + m * 32) = w;
                }
        }
    }
}

__device__ __forceinline__ uint32_t task_get(const uint32_t sb, const uint32_t n, const uint32_t te_addr) {
    mbar_wait(sb + BAR + (MB_TF + (n & 1)) * 8, (n >> 1) & 1);
    const uint32_t t = __shfl_sync(~0u, lds32(sb + TSLOT + (n & 1) * 4), 0);
    if (elect_one()) mbar_arrive_remote(te_addr + (n & 1) * 8);
    return t;
}

__device__ __forceinline__ void worker_producer(const Params& p, const uint32_t sb, const int cluster, const uint32_t rank) {
    const int warp = __shfl_sync(~0u, (int)threadIdx.x >> 5, 0), lane = threadIdx.x & 31;
    const uint32_t bar = sb + BAR;
    const int nwc = p.nclusters - NCHAIN;
    const uint32_t te0 = mapa(bar + MB_TE * 8, 0);
    if (warp == 0) {
        uint32_t it = 0, nb = 0, i2 = 0, ia = 0;
        const uint32_t f1_rem = mapa(bar + MB_F1 * 8, rank ^ 1);
        for (uint32_t n = 0;; n++) {
            if (elect_one()) mbar_expect(bar + (MB_TF + (n & 1)) * 8, 4);
            const uint32_t t = task_get(sb, n, te0);
            const int type = (t >> 9) & 7, b = (t >> 5) & 15, idx = t & 31;
            if (t == TASK_END) break;
            const bool pending = t >> 12;
            const unsigned* dep = &g_flags[F_DONE + type * 16 + b];
            const unsigned depn = p.need[type * 16 + b];
            fence_proxy_async();
            if (type == T_QKV) {
                for (int u = 0; u < 4; u++) mbar_wait(bar + (MB_E2 + ((i2 + u) & 3)) * 8, (((i2 + u) >> 2) & 1) ^ 1);
                if (n == 0 && cluster >= NCHAIN) mbar_wait(bar + MB_P0 * 8, 0);
                if (elect_one()) {
                    const int ec = idx * 128 + rank * 64;
                    for (int i = 0; i < 8; i++) {
                        const uint32_t mb = bar + (MB_BW + i) * 8;
                        mbar_expect(mb, 16384);
                        tma2d(sb + W_B + i * 8192, &p.tmWk, ec, i * 64, mb);
                        tma2d(sb + W_B + 65536 + i * 8192, &p.tmWv, ec, i * 64, mb);
                    }
                }
                __syncwarp();
                for (int tl = qkv_t0(b); tl < qkv_t0(b + 1); tl++) {
                    if (tl < 2) flag_wait(&g_flags[F_H + tl], 2); else if (tl == 2 || tl == qkv_t0(b)) flag_wait(&g_flags[F_HALL], 64);
                    for (int k = rank; k < 8; k += 2) {
                        mbar_wait(bar + (MB_E1 + k) * 8, (it & 1) ^ 1);
                        if (elect_one()) {
                            mbar_expect(bar + (MB_F1 + k) * 8, 8192);
                            mbar_expect_remote(f1_rem + k * 8, 8192);
                            bulk_g2s_mc(sb + W_RING1 + k * 8192, g_h + tl * 32768 + k * 4096, 8192, bar + (MB_F1 + k) * 8, 3);
                        }
                    }
                    it++;
                }
                if (elect_one()) mbar_arrive(bar + MB_PD * 8);
                mbar_wait(bar + MB_QD * 8, nb & 1);
                nb++;
                continue;
            }
            if (type == T_ATT || type == T_Q) {
                const bool att = type == T_ATT, gemm = !att || b < p.qpre0;
                const int nh = att ? p.nh[b] : 4, h0 = (idx * 2 + rank) * nh;
                if (!att) flag_wait(&g_flags[F_HALL], 64);
                if (!gemm) for (int u = 0; u < 4; u++) mbar_wait(bar + (MB_E2 + ((i2 + u) & 3)) * 8, (((i2 + u) >> 2) & 1) ^ 1);
                for (int hh = 0; hh < nh; hh++) {
                    for (int k = gemm ? 0 : 3; k < (gemm ? 8 : 4); k++) {
                        if (gemm) {
                            const uint32_t ii = i2 + k, slot = ii & 3, mb = bar + (MB_F2 + slot) * 8, st = sb + slot * STAGE2;
                            mbar_wait(bar + (MB_E2 + slot) * 8, ((ii >> 2) & 1) ^ 1);
                            if (elect_one()) {
                                mbar_expect(mb, 32768);
                                bulk_g2s_mc(st + rank * 8192, g_h + (b * 2 + rank) * 32768 + k * 4096, 8192, mb, 3);
                                tma2d(st + 16384, &p.tmWq, (h0 + hh) * 128, k * 64, mb);
                                tma2d(st + 24576, &p.tmWq, (h0 + hh) * 128 + 64, k * 64, mb);
                            }
                        }
                        if (k == 3 && att)
                            for (int u = 0; u < 8; u++) {
                                const uint32_t sg = u & 3, part = u >> 2, ab = bar + (MB_AF + sg * 2 + part) * 8;
                                const size_t unit = (size_t)(b * 4 + sg) * H_ + h0 + hh;
                                mbar_wait(ab + (MB_AE - MB_AF) * 8, (ia & 1) ^ 1);
                                if (elect_one()) {
                                    mbar_expect(ab, 10240);
                                    bulk_g2s(sb + sg * STAGE2 + 32768 + part * 8192, reinterpret_cast<const unsigned char*>(g_qkv) + unit * 16384 + part * 8192, 8192, ab);
                                    if (!pending) bulk_g2s(sb + W_KVM + sg * 4096 + part * 2048, g_kvm + unit * 4096 + part * 2048, 2048, ab);
                                }
                            }
                    }
                    if (gemm) i2 += 8;
                    if (att) ia++;
                    if (pending) {
                        flag_wait(dep, depn);
                        if (lane < 8) bulk_g2s(sb + W_KVM + lane * 2048, g_kvm + ((size_t)(b * 4 + (lane >> 1)) * H_ + h0) * 4096 + (lane & 1) * 2048, 2048, bar + (MB_AF + lane) * 8);
                        __syncwarp();
                    }
                }
                if (elect_one()) mbar_arrive(bar + MB_PD * 8);
                if (att) for (int u = 0; u < 8; u++) mbar_wait(bar + (MB_AE + u) * 8, (ia & 1) ^ 1);
                continue;
            } else if (type == T_LN2 || type == T_FIN) {
                const bool ln = type == T_LN2;
                const int rs = p.rs[b], nsum = ln ? p.sk1[b] : p.sk2[b], row0 = b * 128 + (idx * 2 + rank) * rs * 4;
                for (int u = 0; u < 4; u++) mbar_wait(bar + (MB_E2 + ((i2 + u) & 3)) * 8, (((i2 + u) >> 2) & 1) ^ 1);
                const uint32_t sl = (i2 + (lane >> 3)) & 3, mb = bar + (MB_F2 + sl) * 8, q = lane & 7;
                const size_t ro = (size_t)(row0 + (lane >> 3) * rs) * D_;
                if (q == 0) {
                    mbar_expect(mb, nsum * rs * 1024 + rs * (ln ? 1024 : 2048));
                    if (ln) bulk_g2s(sb + sl * STAGE2 + nsum * rs * 1024, p.x + ro, rs * 1024, mb);
                }
                __syncwarp();
                if (pending) flag_wait(dep, depn);
                if (q == 7 && !ln) bulk_g2s(sb + sl * STAGE2 + nsum * rs * 1024, g_x1 + ro, rs * 2048, mb);
                for (int qq = q; qq < nsum; qq += 8) bulk_g2s(sb + sl * STAGE2 + qq * rs * 1024, (ln ? g_p1 : g_p2) + (size_t)qq * S_ * D_ + ro, rs * 1024, mb);
                __syncwarp();
                i2 += 4;
            } else {
                const bool fine = b >= p.fine0;
                const CUtensorMap* ta = type == T_WO ? &p.tmO : type == T_FFN1 ? &p.tmH2 : &p.tmAct;
                const CUtensorMap* tb0 = type == T_WO ? &p.tmWo : type == T_FFN1 ? &p.tmG : &p.tmDn;
                const CUtensorMap* tb1 = type == T_FFN1 ? &p.tmU : tb0;
                const int nk = gemm_nk(p, type, b);
                const int k0 = type == T_FFN1 ? 0 : (fine ? idx >> 1 : idx) * nk;
                int c0, c1;
                if (type == T_FFN1) { c0 = fine ? idx * 128 + rank * 64 : idx * 256 + rank * 128; c1 = c0; }
                else { c0 = fine ? (idx & 1) * 256 + rank * 128 : rank * 256; c1 = c0 + (fine ? 64 : 128); }
                for (int k = 0; k < nk; k++) {
                    const uint32_t ii = i2 + k, slot = ii & 3, mb = bar + (MB_F2 + slot) * 8, dst = sb + slot * STAGE2 + 16384;
                    mbar_wait(bar + (MB_E2 + slot) * 8, ((ii >> 2) & 1) ^ 1);
                    if (elect_one()) {
                        const int kr = (k0 + k) * 64;
                        mbar_expect(mb, fine ? 32768 : STAGE2);
                        if (k >= 4 || !pending) tma2d_mc(sb + slot * STAGE2 + rank * 8192, ta, kr, b * 128 + rank * 64, mb, 3);
                        if (fine) { tma2d(dst, tb0, c0, kr, mb); tma2d(dst + 8192, tb1, c1, kr, mb); }
                        else {
                            tma2d(dst, tb0, c0, kr, mb); tma2d(dst + 8192, tb0, c0 + 64, kr, mb);
                            tma2d(dst + 16384, tb1, c1, kr, mb); tma2d(dst + 24576, tb1, c1 + 64, kr, mb);
                        }
                    }
                    if (k == 3 && pending) {
                        flag_wait(dep, depn);
                        if (lane < 4) {
                            const uint32_t sl = (i2 + lane) & 3;
                            tma2d_mc(sb + sl * STAGE2 + rank * 8192, ta, (k0 + lane) * 64, b * 128 + rank * 64, bar + (MB_F2 + sl) * 8, 3);
                        }
                        __syncwarp();
                    }
                }
                i2 += nk;
            }
            if (elect_one()) mbar_arrive(bar + MB_PD * 8);
        }
    } else if (warp == 1) {
        uint32_t cnt = 0;
        for (uint32_t n = 0;; n++) {
            const uint32_t t = task_get(sb, n, te0);
            const int type = (t >> 9) & 7, b = (t >> 5) & 15;
            if (t == TASK_END) break;
            if (type == T_QKV) {
                for (uint32_t tl = 0, it = 0; tl < 32; it++) {
                    uint32_t c0, c1;
                    asm volatile("ld.acquire.cta.shared.v2.u32 {%0, %1}, [%2];" : "=r"(c0), "=r"(c1) : "r"(sb + W_TILES) : "memory");
                    const uint32_t upto = min(2 * (c0 - cnt), 2 * (c1 - cnt) + 1);
                    if (upto > tl) {
                        if (elect_one()) {
                            flag_signal(&g_flags[F_QKV + tl * 32 + (t & 31)]);
                            for (uint32_t u = tl + 1; u < upto; u++)
                                asm volatile("red.relaxed.gpu.global.add.u32 [%0], 1;" :: "l"(&g_flags[F_QKV + u * 32 + (t & 31)]) : "memory");
                        }
                        __syncwarp();
                        tl = upto;
                    } else __nanosleep(100);
                    if (it > (1u << 23)) __trap();
                }
                cnt += 16;
            }
            mbar_wait(bar + MB_SD2 * 8, n & 1);
            if (type != T_FIN && type != T_QKV && elect_one()) flag_signal(&g_flags[F_DONE + ((type + 1) & 7) * 16 + b]);
            if (type == T_Q && elect_one()) asm volatile("red.relaxed.gpu.global.add.u32 [%0], 1;" :: "l"(&g_flags[F_QD + b]) : "memory");
        }
    } else if (warp == 2 && rank == 0) {
        const uint32_t q0 = nwc < H_ ? nwc : H_;
        bool have_mod = false;
        const bool late = cluster < NCHAIN && (p.mode & 2);
        for (uint32_t n = 0;; n++) {
            if (n > 0) {
                mbar_wait(bar + (MB_TE + ((n - 1) & 1)) * 8, ((n - 1) >> 1) & 1);
                mbar_wait(bar + MB_PD * 8, (n - 1) & 1);
            }
            uint32_t t = TASK_END, prev = 0xffffffffu;
            const bool fixed = n == 0 && (p.mode & 1) && cluster >= NCHAIN && cluster - NCHAIN < H_;
            if (fixed) t = T_QKV << 9 | (cluster - NCHAIN);
            for (unsigned it = 1; !fixed; ++it) {
                uint32_t d[4], c[4], key[4], openm[3], rdym[3];
                const uint32_t near = ld_volatile_u32(&g_flags[F_NEAR]);
#pragma unroll
                for (int i = 0; i < 4; i++) {
                    d[i] = ld_volatile_u32(&g_flags[i < 3 ? F_DONE + lane + i * 32 : F_QD + (lane & 15)]);
                    c[i] = ld_volatile_u32(&g_flags[F_CLAIM + lane + i * 32]);
                }
                bool open = false;
#pragma unroll
                for (int i = 0; i < 4; i++) {
                    const uint32_t e = lane + i * 32, cn = p.cnt[e];
                    const bool op = c[i] < cn, rd = d[i] >= p.need[e];
                    if (i < 3) { openm[i] = __ballot_sync(~0u, op); rdym[i] = __ballot_sync(~0u, rd); }
                    const bool mine = !late || (e & 15) >= p.fine0 || (e >> 4) == T_LN2 || (e >> 4) == T_FIN;
                    key[i] = op && rd && mine ? (uint32_t)p.prio[e] << 13 | e << 6 | (cn - c[i]) : 0xffffffffu;
                    open |= op && mine;
                }
                if (!__any_sync(~0u, open)) break;
                const uint32_t qdone = __ballot_sync(~0u, d[3] >= 8u || lane < p.qpre0);
                uint32_t best = __reduce_min_sync(~0u, min(min(key[0], key[1]), min(key[2], key[3])));
                const bool idle = n == 0 || mbar_test(bar + MB_SD2 * 8, (n - 1) & 1);
                uint32_t pend = 0;
                if (idle && (best >> 13) != 0) {
                    const bool none = best == 0xffffffffu;
                    const uint32_t fm = none ? (late ? 0xffffu << p.fine0 & 0xffffu : RESV_MASK) : 0x8000u, f2 = fm | fm << 16;
                    const uint32_t att = openm[0] & 0xffffu;
                    const uint32_t first = ((none ? att & (0u - att) & (0xffffu << p.fine0) : 0u) | (near ? 0x8000u : 0u)) & qdone;
                    const uint32_t run0 = ~openm[0] & rdym[0], run1 = ~openm[1] & rdym[1], run2 = ~openm[2] & rdym[2];
                    const uint32_t c0 = openm[0] & ~rdym[0] & f2 & (first | run0 << 16);
                    const uint32_t c1 = openm[1] & ~rdym[1] & f2 & (run0 >> 16 | run1 << 16);
                    const uint32_t c2 = openm[2] & ~rdym[2] & f2 & (run1 >> 16 | run2 << 16);
                    if (c0 | c1 | c2) { best = (c0 ? __ffs(c0) - 1 : c1 ? 31 + __ffs(c1) : 63 + __ffs(c2)) << 6 | 63; pend = 1u << 12; }
                }
                if (best == 0xffffffffu) __nanosleep(100);
                else if (!idle && best >> 6 != prev) __nanosleep(400);
                else {
                    uint32_t skip = 0, cur = best;
                    while (cur != 0xffffffffu) {
                        const uint32_t e = (cur >> 6) & 127;
                        if (skip >= (cur & 63)) skip -= cur & 63;
                        else {
                            uint32_t got = 0;
                            if (lane == 0) got = atomicAdd(&g_flags[F_CLAIM + e], 1u);
                            got = __shfl_sync(~0u, got, 0);
                            if (got < p.cnt[e]) { t = pend | e << 5 | (got + (e == 96 ? q0 : 0u)); break; }
                            skip = got - p.cnt[e];
                        }
                        const uint32_t lim = pend ? 0u : cur;
                        pend = 0;
                        uint32_t nx = 0xffffffffu;
#pragma unroll
                        for (int i = 0; i < 4; i++) if (key[i] > lim) nx = min(nx, key[i]);
                        cur = __reduce_min_sync(~0u, nx);
                    }
                    if (cur != 0xffffffffu) break;
                }
                prev = best >> 6;
                if (it > (1u << 22)) __trap();
            }
            if (!have_mod && ((t >> 9) & 7) < T_QKV) { flag_wait(&g_flags[F_MOD], 48); have_mod = true; }
            if (lane == 0) {
                asm volatile("fence.acquire.gpu;" ::: "memory");
                const uint32_t mb = bar + (MB_TF + (n & 1)) * 8;
                st_async_b32(mapa(sb + TSLOT + (n & 1) * 4, 1), t, mapa(mb, 1));
                st_async_b32(mapa(sb + TSLOT + (n & 1) * 4, 0), t, mapa(mb, 0));
            }
            __syncwarp();
            if (t == TASK_END) break;
        }
    }
}

__device__ __forceinline__ void worker_consumer(const Params& p, const uint32_t sb, const int cluster, const uint32_t rank) {
    const int ct = threadIdx.x - 128, lane = ct & 31, g = lane >> 2, j = lane & 3;
    const int wgi = __shfl_sync(~0u, ct >> 7, 0), w4 = __shfl_sync(~0u, (ct >> 5) & 3, 0);
    const uint32_t bar = sb + BAR;
    const int nwc = p.nclusters - NCHAIN;
    const bool elect = (ct & 127) == 0;
    if (cluster >= NCHAIN && (p.mode & 1)) phase0(p, sb, (cluster - NCHAIN) * 2 + rank, nwc * 2, ct);
    const uint32_t e1_0 = mapa(bar + MB_E1 * 8, 0), e1_d = mapa(bar + MB_E1 * 8, 1) - e1_0;
    uint32_t nb = 0;
    const uint32_t te0 = mapa(bar + MB_TE * 8, 0);
    const uint32_t e2_rem = mapa(bar + MB_E2 * 8, rank ^ 1);
    uint32_t i2 = 0, ia = 0;
    for (uint32_t n = 0;; n++) {
        mbar_wait(bar + (MB_TF + (n & 1)) * 8, (n >> 1) & 1);
        const uint32_t t = __shfl_sync(~0u, lds32(sb + TSLOT + (n & 1) * 4), 0);
        bar_sync(6 + wgi, 128);
        if (elect) mbar_arrive_remote(te0 + (n & 1) * 8);
        const int type = (t >> 9) & 7, b = (t >> 5) & 15, idx = t & 31;
        if (t == TASK_END) break;
        const bool fine = b >= p.fine0;
        DBG(ct == 0 && rank == 0, 8192 + (t & 4095) * 4, gtime());
        DBG(ct == 0 && rank == 0, 8192 + (t & 4095) * 4 + 3, blockIdx.x);
        if (type == T_QKV) {
            const int head = idx, tb = qkv_t0(b), te = qkv_t0(b + 1);
            for (int t = tb + wgi; t < te; t += 2) {
                constexpr bool real = true;
                float acc[64];
#pragma unroll
                for (int i = 0; i < 64; i++) acc[i] = 0.f;
                if (t > tb) bar_sync(8 + wgi, 256);
                const bool last = t == te - 1 || !real, first = real && t < tb + 2;
                const uint32_t ph = (nb * 32 + t) & 1;
                DBG(blockIdx.x == 70 && elect && real, 4096 + t * 4, clock64());
                const uint64_t da = gmma_desc(sb + W_RING1, 16, 512, 2), db = gmma_desc(sb + W_B, 65536, 1024, 1);
                if (real) mbar_wait(bar + MB_F1 * 8, ph);
                if (first) mbar_wait(bar + MB_BW * 8, nb & 1);
                DBG(ct == 0 && t == 0, 40000 + blockIdx.x * 16 + 5, gtime());
                wg_fence();
#pragma unroll
                for (int k = 0; k < 8; k++) {
                    wgmma_n128(acc, da + k * 512, db + k * 512);
                    wgmma_n128(acc, da + k * 512 + 2, db + k * 512 + 128);
                    if (k < 7 && real) mbar_wait(bar + (MB_F1 + k + 1) * 8, ph);
                    if (k < 7 && first) mbar_wait(bar + (MB_BW + k + 1) * 8, nb & 1);
                    if (k == 6 && !last) bar_arrive(8 + (wgi ^ 1), 256);
                    wgmma_n128(acc, da + k * 512 + 256, db + k * 512 + 256);
                    wgmma_n128(acc, da + k * 512 + 258, db + k * 512 + 384);
                    wg_commit();
                    if (k > 0) {
                        wg_wait<1>();
                        if (elect && real) mbar_arrive_remote(e1_0 + ((k - 1) & 1) * e1_d + (k - 1) * 8);
                    }
                }
                wg_wait<0>();
                if (elect && real) {
                    mbar_arrive_remote(e1_0 + e1_d + 7 * 8);
                    if (t >= te - 2) { mbar_arrive_remote(e1_0 + (MB_QD - MB_E1) * 8); mbar_arrive_remote(e1_0 + e1_d + (MB_QD - MB_E1) * 8); }
                }
                __syncwarp();
                DBG(blockIdx.x == 70 && elect && real, 4096 + t * 4 + 1, clock64());
#pragma unroll
                for (int u = 0; u < 2; u++) {
                    const int tok = t * 64 + w4 * 16 + u * 8 + g, row = tok & 31;
                    unsigned char* base = reinterpret_cast<unsigned char*>(g_qkv) + ((size_t)(tok >> 5) * H_ + head) * 16384 + row * 256 + rank * 128;
#pragma unroll
                    for (int m = 0; m < 4; m++) {
                        const int a = m * 16 + u * 2;
                        const uint4 v = quad_transpose(pack_bf16(acc[a], acc[a + 1]), pack_bf16(acc[a + 4], acc[a + 5]),
                                                       pack_bf16(acc[a + 8], acc[a + 9]), pack_bf16(acc[a + 12], acc[a + 13]), j);
                        if (real) *reinterpret_cast<uint4*>(base + (m >> 1) * 8192 + ((((m & 1) * 4 + j) ^ (row & 7)) << 4)) = v;
                    }
                }
                bar_sync(6 + wgi, 128);
                if (elect) asm volatile("red.release.cta.shared.add.u32 [%0], 1;" :: "r"(sb + W_TILES + wgi * 4) : "memory");
                DBG(elect && (t == 0 || t == 31), 40000 + blockIdx.x * 16 + 6 + (t == 31), gtime());
                DBG(blockIdx.x == 70 && elect && real, 4096 + t * 4 + 2, clock64());
                DBG(blockIdx.x == 70 && elect && real, 4096 + t * 4 + 3, gtime());
            }
            nb++;
        } else if (type == T_ATT || type == T_Q) {
            const bool att = type == T_ATT, gemm = !att || b < p.qpre0;
            const int nh = att ? p.nh[b] : 4, h0 = (idx * 2 + rank) * nh, wp = wgi * 2 + (w4 >> 1);
#pragma unroll 1
            for (int hh = 0; hh < nh; hh++) {
                uint32_t q[8][4];
                uint4* qg = g_q + (((size_t)b * H_ + h0 + hh) * 8 + wgi * 4 + w4) * 256 + lane;
                if (gemm) {
                    float acc[64];
#pragma unroll
                    for (int i = 0; i < 64; i++) acc[i] = 0.f;
#pragma unroll 1
                    for (int k = 0; k < 8; k++) {
                        const uint32_t ii = i2 + k, slot = ii & 3, st = sb + slot * STAGE2;
                        mbar_wait(bar + (MB_F2 + slot) * 8, (ii >> 2) & 1);
                        wg_fence();
#pragma unroll
                        for (int kk = 0; kk < 4; kk++)
                            wgmma_n128(acc, gmma_desc(st + wgi * 8192 + (kk >> 1) * 4096 + (kk & 1) * 32, 16, 512, 2), gmma_desc(st + 16384 + kk * 2048, 8192, 1024, 1));
                        wg_commit();
                        wg_wait<0>();
                        if (elect) { mbar_arrive(bar + (MB_E2 + slot) * 8); mbar_arrive_remote(e2_rem + slot * 8); }
                        __syncwarp();
                    }
                    i2 += 8;
#pragma unroll
                    for (int i = 0; i < 32; i++) q[i >> 2][i & 3] = pack_bf16(acc[2 * i], acc[2 * i + 1]);
                } else {
#pragma unroll
                    for (int i = 0; i < 8; i++) { const uint4 v = __ldcg(qg + i * 32); q[i][0] = v.x; q[i][1] = v.y; q[i][2] = v.z; q[i][3] = v.w; }
                }
                DBG(ct == 0 && rank == 0 && hh == 0, 8192 + (t & 4095) * 4 + 1, gtime());
                if (!att) {
#pragma unroll
                    for (int i = 0; i < 8; i++) qg[i * 32] = make_uint4(q[i][0], q[i][1], q[i][2], q[i][3]);
                    continue;
                }
#pragma unroll 1
                for (int real = (t >> 12) ? 0 : 1; real < 2; real++)
                    attend(q, sb + wp * STAGE2 + 32768, sb + W_KVM + wp * 4096, w4 & 1, lane,
                           g_o + (size_t)((b * 4 + wp) * 32) * 4096 + (h0 + hh) * 128, bar + (MB_AF + wp * 2) * 8, ia & 1, real);
                ia++;
            }
        } else if (type == T_LN2 || type == T_FIN) {
            const bool ln = type == T_LN2;
            const int rs = p.rs[b], nsum = ln ? p.sk1[b] : p.sk2[b], wp = wgi * 2 + (w4 >> 1);
            const uint32_t ii = i2 + wp, slot = ii & 3;
            float4 md[12];
#pragma unroll
            for (int i = 0; i < 12; i++) md[i] = __ldcg(reinterpret_cast<const float4*>(g_mod + (i < 4 && !ln ? 5 : 2 + (i >> 2)) * D_ + lane * 4 + (i & 3) * 128));
#pragma unroll 1
            for (int real = (t >> 12) ? 0 : 1; real < 2; real++) {
                if (real) mbar_wait(bar + (MB_F2 + slot) * 8, (ii >> 2) & 1);
                DBG(ct == 0 && rank == 0, 8192 + (t & 4095) * 4 + 1, gtime());
                row_task(p, sb + slot * STAGE2, ln, nsum, rs, w4 & 1, b * 128 + ((idx * 2 + rank) * 4 + wp) * rs, lane, md, real);
            }
            __syncwarp();
            if (lane == 0) { mbar_arrive(bar + (MB_E2 + slot) * 8); mbar_arrive_remote(e2_rem + slot * 8); }
            i2 += 4;
        } else {
            const int nk = gemm_nk(p, type, b);
            const int row = b * 128 + wgi * 64 + w4 * 16 + g;
            if (fine) gemm_task<128>(sb, i2, nk, type, idx, row, rank, wgi, j, elect, e2_rem, t);
            else gemm_task<256>(sb, i2, nk, type, idx, row, rank, wgi, j, elect, e2_rem, t);
            i2 += nk;
        }
        bar_sync(6 + wgi, 128);
        if (elect) mbar_arrive(bar + MB_SD2 * 8);
        DBG(ct == 0 && rank == 0, 8192 + (t & 4095) * 4 + 2, gtime());
    }
}

__global__ void __launch_bounds__(NTHREADS, 1) fused_kernel(const __grid_constant__ Params p) {
    extern __shared__ __align__(1024) unsigned char smem[];
    const uint32_t sb = smem_u32(smem);
    DBG(threadIdx.x == 64, 40000 + blockIdx.x * 16 + 8, gtime());
    if (blockIdx.x >= 2 * NCHAIN && threadIdx.x >= 128) {
        const int w = blockIdx.x - 2 * NCHAIN, ct = threadIdx.x - 128;
        if (w < 64) asm volatile("prefetch.global.L2 [%0];" :: "l"(p.x + (size_t)w * 32 * D_ + ct * 64));
        if (w >= 4 && w < 20) {
            asm volatile("prefetch.global.L2 [%0];" :: "l"(p.wmod + (size_t)ct * 3072 + (w - 4) * 64));
            asm volatile("prefetch.global.L2 [%0];" :: "l"(p.wmod + (size_t)(ct + 256) * 3072 + (w - 4) * 64));
            if (ct < 8) asm volatile("prefetch.global.L2 [%0];" :: "l"(p.c + ct * 64));
        }
    }
    if (threadIdx.x == 0) {
        const uint32_t bar = sb + BAR;
        for (int i = 0; i < MB_COUNT; i++) {
            uint32_t c = 1;
            if (i == MB_QD) c = 4;
            else if (i == MB_RED) c = 4;
            else if (i == MB_MEM) c = 4;
            else if (i >= MB_E1 && i < MB_E1 + 8) c = 2;
            else if (i >= MB_E2 && i < MB_E2 + 4) c = 4;
            else if (i == MB_SD2 || (i >= MB_AE && i < MB_AE + 8)) c = 2;
            else if (i >= MB_TE) c = 8;
            mbar_init(bar + i * 8, c);
        }
        sts64(sb + W_TILES, 0, 0); sts32(sb + C_TGT, 0);
        asm volatile("fence.mbarrier_init.release.cluster;" ::: "memory");
    }
    __syncthreads();
    cluster_sync_relaxed();
    DBG(threadIdx.x == 0, 32768 + blockIdx.x * 4, gtime());
    if (cluster_id() < NCHAIN && (p.mode & 2)) chain_role(p, sb);
    DBG(threadIdx.x == 0, 32768 + blockIdx.x * 4 + 1, gtime());
    if (threadIdx.x < 128) {
        asm volatile("setmaxnreg.dec.sync.aligned.u32 56;");
        worker_producer(p, sb, cluster_id(), cta_rank());
        __syncwarp();
    } else {
        asm volatile("setmaxnreg.inc.sync.aligned.u32 224;");
        worker_consumer(p, sb, cluster_id(), cta_rank());
    }
    __syncthreads();
    cluster_sync_relaxed();
    DBG(threadIdx.x == 0, 32768 + blockIdx.x * 4 + 2, gtime());
    if (p.mode & 8) {
        if (threadIdx.x == 0) {
            asm volatile("fence.acq_rel.gpu;" ::: "memory");
            sts32(sb + TSLOT + 16, atomicAdd(&g_flags[F_EXIT], 1u) == gridDim.x - 1);
        }
        __syncthreads();
        if (lds32(sb + TSLOT + 16)) {
            for (int i = threadIdx.x; i < NFLAGS; i += NTHREADS) g_flags[i] = 0;
            for (int i = threadIdx.x; i < 2 * D_; i += NTHREADS) g_mod[i] = 0.f;
        }
    }
}

typedef CUresult (*EncodeFn)(CUtensorMap*, CUtensorMapDataType, cuuint32_t, void*, const cuuint64_t*, const cuuint64_t*,
                             const cuuint32_t*, const cuuint32_t*, CUtensorMapInterleave, CUtensorMapSwizzle,
                             CUtensorMapL2promotion, CUtensorMapFloatOOBfill);

void make_map(EncodeFn enc, CUtensorMap* m, const void* ptr, uint64_t rows, uint64_t cols, uint32_t box_cols, uint32_t box_rows, CUtensorMapSwizzle sw) {
    cuuint64_t dims[2] = {cols, rows};
    cuuint64_t strides[1] = {cols * 2};
    cuuint32_t box[2] = {box_cols, box_rows};
    cuuint32_t es[2] = {1, 1};
    enc(m, CU_TENSOR_MAP_DATA_TYPE_BFLOAT16, 2, const_cast<void*>(ptr), dims, strides, box, es, CU_TENSOR_MAP_INTERLEAVE_NONE, sw,
        CU_TENSOR_MAP_L2_PROMOTION_L2_256B, CU_TENSOR_MAP_FLOAT_OOB_FILL_NONE);
}

Params g_params;
bool g_ready = false;
void* g_in[13];
int g_qpre0 = 4, g_fine0 = 13, g_med0 = 6, g_x15 = 0;
int g_mode = 15, g_delay = 700 | (100 << 12) | (12 << 24);

void build_tasks(Params& P) {
    P.fine0 = g_fine0;
    for (int b = 0; b < 16; b++) {
        const bool f = b >= P.fine0;
        const bool md = b >= g_med0;
        P.nh[b] = f ? 1 : md ? 2 : 4; P.sk1[b] = f ? 8 : md ? 4 : 2; P.sk2[b] = f ? 7 : md ? 4 : 2; P.rs[b] = f ? 2 : md ? 4 : 8;
        if (b >= 16 - g_x15) { P.sk1[b] = 16; P.rs[b] = 1; }
        const int cnt[6] = {16 / P.nh[b], P.sk1[b] * (f ? 2 : 1), 16 / P.rs[b], f ? 14 : 7, P.sk2[b] * (f ? 2 : 1), 16 / P.rs[b]};
        for (int t = 0; t < 6; t++) {
            P.cnt[t * 16 + b] = (unsigned char)((g_mode & 4) ? cnt[t] : 0);
            P.need[t * 16 + b] = (unsigned char)(t == 0 ? 64 : 2 * cnt[t - 1]);
            const int rem_c[6] = {62, 52, 30, 24, 15, 3}, rem_m[6] = {55, 43, 29, 23, 12, 4}, rem_f[6] = {28, 22, 17, 13, 8, 5};
            P.prio[t * 16 + b] = (unsigned char)(63 - (f ? rem_f[t] : md ? rem_m[t] : rem_c[t]));
        }
    }
    const int nwc = P.nclusters - NCHAIN;
    P.qpre0 = g_qpre0;
    for (int e = 96; e < 128; e++) {
        P.cnt[e] = (unsigned char)(e == 96 ? ((g_mode & 1) && nwc < H_ ? H_ - nwc : 0) : (e >= 112 + P.qpre0 && (g_mode & 4)) ? 4 : 0);
        P.need[e] = 0;
        P.prio[e] = (unsigned char)(e == 96 ? 0 : 62);
        if (e >= 112 + P.qpre0) P.need[e - 112] += 8;
    }
}

}

extern "C" void kernel_launch(void* const* d_in, const int* in_sizes, int n_in, void* d_out, int out_size) {
    (void)in_sizes; (void)n_in; (void)out_size;
    Params& P = g_params;
    bool same = g_ready;
    for (int i = 0; i < 13 && same; i++) same = g_in[i] == d_in[i];
    if (!same) {
        for (int i = 0; i < 13; i++) g_in[i] = d_in[i];
        void* fn = nullptr;
        cudaDriverEntryPointQueryResult qr;
        cudaGetDriverEntryPoint("cuTensorMapEncodeTiled", &fn, cudaEnableDefault, &qr);
        EncodeFn enc = (EncodeFn)fn;
        void *o, *h2, *act;
        cudaGetSymbolAddress(&o, g_o); cudaGetSymbolAddress(&h2, g_h2); cudaGetSymbolAddress(&act, g_act);
        const CUtensorMapSwizzle S128 = CU_TENSOR_MAP_SWIZZLE_128B;
        make_map(enc, &P.tmWq, d_in[2], 512, 4096, 64, 64, S128);
        make_map(enc, &P.tmWk, d_in[3], 512, 4096, 64, 64, S128);
        make_map(enc, &P.tmWv, d_in[4], 512, 4096, 64, 64, S128);
        make_map(enc, &P.tmWo, d_in[5], 4096, 512, 64, 64, S128);
        make_map(enc, &P.tmG, d_in[8], 512, F_, 64, 64, S128);
        make_map(enc, &P.tmU, d_in[9], 512, F_, 64, 64, S128);
        make_map(enc, &P.tmDn, d_in[10], F_, 512, 64, 64, S128);
        make_map(enc, &P.tmO, o, S_, 4096, 64, 64, S128);
        make_map(enc, &P.tmH2, h2, S_, 512, 64, 64, S128);
        make_map(enc, &P.tmAct, act, S_, F_, 64, 64, S128);
        P.x = (const bf16*)d_in[0]; P.mem0 = (const bf16*)d_in[1]; P.c = (const bf16*)d_in[11]; P.wmod = (const bf16*)d_in[12];
        cudaFuncSetAttribute(fused_kernel, cudaFuncAttributeMaxDynamicSharedMemorySize, SMEM_BYTES);
        cudaLaunchConfig_t q = {};
        q.gridDim = dim3(132); q.blockDim = dim3(NTHREADS); q.dynamicSmemBytes = SMEM_BYTES;
        cudaLaunchAttribute qa[1];
        qa[0].id = cudaLaunchAttributeClusterDimension; qa[0].val.clusterDim.x = 2; qa[0].val.clusterDim.y = 1; qa[0].val.clusterDim.z = 1;
        q.attrs = qa; q.numAttrs = 1;
        int nc = 0;
        cudaOccupancyMaxActiveClusters(&nc, fused_kernel, &q);
        if (nc > 66) nc = 66;
        P.nclusters = nc;
        build_tasks(P);
        g_ready = true;
    }
    P.out = (bf16*)d_out;
    P.mode = g_mode; P.delay = g_delay; P.zero = 0;
    cudaLaunchConfig_t cfg = {};
    cfg.gridDim = dim3(P.nclusters * 2); cfg.blockDim = dim3(NTHREADS); cfg.dynamicSmemBytes = SMEM_BYTES;
    cfg.stream = cudaStreamPerThread;
    cudaLaunchAttribute at[1];
    at[0].id = cudaLaunchAttributeClusterDimension; at[0].val.clusterDim.x = 2; at[0].val.clusterDim.y = 1; at[0].val.clusterDim.z = 1;
    cfg.attrs = at; cfg.numAttrs = 1;
    cudaLaunchKernelEx(&cfg, fused_kernel, P);
}
```
